```python
import torch

def _softmax(x, axis=-1):
    return torch.softmax(x, dim=axis)
def _gelu(x):
    return torch.nn.functional.gelu(x, approximate="tanh")
def _silu(x):
    return torch.nn.functional.silu(x)
def _sigmoid(x):
    return torch.sigmoid(x)
def _layernorm(x, axis=-1, eps=1e-5):
    m = x.mean(dim=axis, keepdim=True)
    v = x.var(dim=axis, keepdim=True, unbiased=False)
    return (x - m) / torch.sqrt(v + eps)
def _scatter_add(tgt, idx, src, axis=0):
    return tgt.clone().index_add_(axis, idx, src)
def _segment_sum(src, seg, n):
    out = torch.zeros((n,) + src.shape[1:], dtype=src.dtype)
    return out.index_add_(0, seg, src)
def _pad(x, pw):
    flat = tuple(v for pair in reversed(pw) for v in pair)
    return torch.nn.functional.pad(x, flat)

kernel_name = 'standalone__structured_sparse_n_m__ragged'

def setup_inputs():

    _w = (lambda a: (lambda t: t.to(torch.bfloat16) if t.is_floating_point() else t)(torch.as_tensor(a)))
    B, S, D = 16, 4096, 576
    assert D % 4 == 0, "d_model must be divisible by M=4 for 2:4 sparsity"
    return {
        "x": _w((lambda *s: torch.randn(*s, dtype=torch.bfloat16) * 0.05)(B, S, D)),
        "w": _w((lambda *s: torch.randn(*s, dtype=torch.bfloat16) * 0.05)(D, D)),
        "b": _w((lambda *s: torch.randn(*s, dtype=torch.bfloat16) * 0.05)(D)),
    }

def reference(x, w, b):
    B, S, D = x.shape
    N, M = 2, 4
    G = D // M
    wg = w.reshape(G, M, D)
    mag = torch.abs(wg)
    order = torch.argsort(mag, 1)
    thr = (lambda x, i, axis: torch.take_along_dim(x, i, dim=axis))(mag, order[:, M - N:M - N + 1, :], 1)
    mask = (lambda x, dt: x.to(dt))(mag >= thr, w.dtype)
    wp = (wg * mask).reshape(D, D)
    return torch.einsum("bsd,df->bsf", x, wp) + b
```

```cpp
#include <cuda_runtime.h>
#include <cuda_bf16.h>
#include <cuda.h>
#include <stdint.h>

constexpr int D = 576;
constexpr int NT = 32;
constexpr int NSLOT = 5;
constexpr int XEARLY = 2;
constexpr int NSTAT = 4;
constexpr int DELTA = 24;
constexpr int HT = 43;
constexpr int LEAD0 = 140, LEAD1 = 310, LEADE = 15, PACE = 1200;
constexpr double TAFRAC = 0.249, TEFRAC = 0.97;
constexpr int NPR = 2, PWAIT = 1300;
constexpr int KSTEPS = 18;
constexpr int CL = 3;
constexpr int TILE_BYTES = NT * D * 2;
constexpr int STG_BYTES = NT * 128;
constexpr int NACC = NT / 2;
constexpr int NB = NT / 8;
constexpr int NCONS = 384;
constexpr int NTHREADS = 512;
constexpr int NTAB = 1024;
constexpr uint32_t NO_TILE = 0xFFFFFu;

constexpr int OFF_X = 0;
constexpr int OFF_WST = OFF_X + (NSLOT - 1) * TILE_BYTES;
constexpr int OFF_STG = OFF_X + NSLOT * TILE_BYTES;
constexpr int OFF_TAB = OFF_STG + 3 * STG_BYTES;
constexpr int OFF_TK = OFF_TAB + 16 * NTAB;
constexpr int OFF_MSK = OFF_TK + 128;
constexpr int OFF_INFO = OFF_MSK + 2 * 36 * 8;
constexpr int OFF_FULL = OFF_INFO + 32;
constexpr int OFF_EMPTY = OFF_FULL + 8 * NSLOT;
constexpr int OFF_MBAR = OFF_EMPTY + 8 * NSLOT;
constexpr int OFF_GO = OFF_MBAR + 16;
constexpr int OFF_PLAN = OFF_GO + 8;
constexpr int OFF_PLAN2 = OFF_PLAN + 8;
constexpr int SMEM_BYTES = OFF_PLAN2 + 8 + 1024;
static_assert(SMEM_BYTES <= 232448 && TILE_BYTES >= 192 * 128 && XEARLY % 2 == 0 && XEARLY < NSLOT && NSLOT < 8 && NB == 4 && OFF_INFO % 16 == 0, "layout");

__device__ __align__(128) uint4    g_afrag[9 * KSTEPS * 128];
__device__ __align__(128) uint4    g_aux[36 * 6 * 32];
__device__ __align__(128) uint2    g_rval[36 * 36 * 32];
__device__ __align__(128) uint32_t g_roff[36 * 36 * 32];
__device__ __align__(128) uint32_t g_ready[9 * 32];
__device__ __align__(128) uint32_t g_passed;
__device__ __align__(128) uint32_t g_ticket;
__device__ __align__(128) uint32_t g_done;
__device__ __align__(128) unsigned long long g_plan;

__device__ __forceinline__ uint32_t max2(uint32_t a, uint32_t b) { uint32_t d; asm("max.u16x2 %0, %1, %2;" : "=r"(d) : "r"(a), "r"(b)); return d; }
__device__ __forceinline__ uint32_t min2(uint32_t a, uint32_t b) { uint32_t d; asm("min.u16x2 %0, %1, %2;" : "=r"(d) : "r"(a), "r"(b)); return d; }
__device__ __forceinline__ uint32_t sign2(uint32_t a) { uint32_t d; asm("prmt.b32 %0, %1, %1, 0xBB99;" : "=r"(d) : "r"(a)); return d; }
__device__ __forceinline__ void load_unit(uint32_t wsm, int ls, int unit, int lane, uint32_t (&m)[4]) {
    const int row = ls * 32 + (lane >> 4) * 16 + ((lane & 7) >> 1) * 4 + ((lane >> 3) & 1) * 2 + (lane & 1);
    const uint32_t ad = wsm + row * 128 + ((unit ^ ((row & 1) | ((row >> 1) & 6))) << 4);
    asm volatile("ldmatrix.sync.aligned.m8n8.x4.trans.shared.b16 {%0,%1,%2,%3}, [%4];" : "=r"(m[0]), "=r"(m[1]), "=r"(m[2]), "=r"(m[3]) : "r"(ad) : "memory");
}
__device__ __forceinline__ void zip4(uint32_t a01, uint32_t a23, uint32_t b01, uint32_t b23, uint32_t (&x)[4]) {
    x[0] = __byte_perm(a01, b01, 0x5410); x[1] = __byte_perm(a01, b01, 0x7632); x[2] = __byte_perm(a23, b23, 0x5410); x[3] = __byte_perm(a23, b23, 0x7632);
}
__device__ __forceinline__ void middle2(const uint32_t (&x)[4], uint32_t (&m)[4], uint32_t& u, uint32_t& v) {
#pragma unroll
    for (int i = 0; i < 4; i++) m[i] = x[i] & 0x7FFF7FFFu;
    u = min2(max2(m[0], m[1]), max2(m[2], m[3])); v = max2(min2(m[0], m[1]), min2(m[2], m[3]));
}
__device__ __forceinline__ int ties(uint32_t x0, uint32_t x1, uint32_t x2, uint32_t x3) {
    const uint32_t x[4] = {x0, x1, x2, x3};
    uint32_t m[4], u, v;
    middle2(x, m, u, v);
    const uint32_t t = u ^ v, f = u ^ min2(min2(m[0], m[1]), min2(m[2], m[3]));
    const bool t0 = (t & 0xFFFFu) == 0 && (v & 0xFFFFu) != 0, t1 = t < 0x10000u && v >= 0x10000u;
    return t0 + t1 + 2 * ((t0 && (f & 0xFFFFu) == 0) || (t1 && f < 0x10000u));
}
__device__ __forceinline__ void split(const uint32_t (&x)[4], bool dbl, bool P, uint32_t& alo, uint32_t& ahi, uint32_t& nib, uint32_t& va, uint32_t& vb) {
    uint32_t m[4], u, v;
    middle2(x, m, u, v);
    const uint32_t c = 0x80008000u - max2(max2(u, v), 0x00010001u);
    uint32_t k0 = sign2(m[0] + c), k1 = sign2(m[1] + c), k2 = sign2(m[2] + c), k3 = sign2(m[3] + c);
    const uint32_t three = (k0 & k1 & (k2 | k3)) | (k2 & k3 & (k0 | k1)), four = k0 & k1 & k2 & k3;
    const bool a2 = !dbl && P;
    const uint32_t pa = a2 ? k2 : k0, pb = dbl ? k2 : P ? k3 : k1;
    const uint32_t ra = three & pa, rb = three & pb & (four | ~pa);
    va = (a2 ? x[2] : x[0]) & ra; vb = (dbl ? x[2] : P ? x[3] : x[1]) & rb;
    if (a2) k2 &= ~ra; else k0 &= ~ra;
    if (dbl) k2 &= ~rb; else if (P) k3 &= ~rb; else k1 &= ~rb;
    const uint32_t s1 = k1 & k0, s2 = k2 & (k0 | k1);
    const uint32_t t = (k1 & x[1]) | (~k1 & k2 & x[2]);
    const uint32_t x0 = (k0 & x[0]) | (~k0 & t), x1 = (s1 & x[1]) | (s2 & x[2]) | (k3 & x[3]);
    nib = (~k0 & k1 & 0x00010001u) | (~k0 & ~k1 & 0x00020002u) | (~s2 & 0x00040004u) | (~s1 & 0x00080008u);
    alo = __byte_perm(x0, x1, 0x5410); ahi = __byte_perm(x0, x1, 0x7632);
}
__device__ __forceinline__ uint32_t resid_off(int g, int P, int r) {
    int k0 = 4 * g + 2 * P;
    int chunk = k0 >> 6, byte = (k0 & 63) * 2;
    return chunk * 1024 + r * 128 + (((byte >> 4) ^ r) << 4) + (byte & 15);
}
__device__ __forceinline__ void emit_step(const uint32_t (&lo)[4], const uint32_t (&hi)[4], uint32_t mm, uint32_t dd, int rb, int ks, int lane, uint32_t units, uint2 bias2) {
    uint32_t* const aux = (uint32_t*)(g_aux + rb * 6 * 32);
    auto put_slot = [&](int j, int ln, uint32_t v, uint32_t off) {
        uint16_t* o = j < 6 ? (uint16_t*)aux + (3 * 32 + ln) * 8 + j : (uint16_t*)g_roff + ((rb * 36 + (j >> 1)) * 32 + ln) * 2 + (j & 1);
        uint16_t* w = j < 6 ? (uint16_t*)aux + ((4 + (j >> 2)) * 32 + ln) * 8 + (j & 2) * 2 + (j & 1) : (uint16_t*)g_rval + ((rb * 36 + (j >> 1)) * 32 + ln) * 4 + (j & 1);
        o[0] = (uint16_t)off; w[0] = (uint16_t)v; w[2] = (uint16_t)(v >> 16);
    };
    const int r = lane >> 2, q = lane & 3, g0 = ks * 8 + q;
    const uint32_t gm = __shfl_sync(~0u, mm | (dd << 8), ks);
    const uint32_t md = mm | (dd << 8), c2 = __popc(md & 0x5555u) | (__popc(md & 0xAAAAu) << 16);
    const uint32_t tot = __reduce_add_sync(~0u, c2), pre = __reduce_add_sync(~0u, lane < ks ? c2 : 0u);
    const int ne = tot & 0xFFFF, no = tot >> 16;
    const uint32_t par = (q & 1) ? 0xAAAAu : 0x5555u;
    const int base = (q & 1) ? pre >> 16 : pre & 0xFFFF;
    const int rk0 = base + __popc(gm & par & (((1u << q) - 1) * 0x101u)), rk1 = base + __popc(gm & par & (((16u << q) - 1) * 0x101u));
    const bool d0 = (gm >> (8 + q)) & 1, d1 = (gm >> (12 + q)) & 1;
    uint32_t a[4], rs[4], x[4], w0, w1;
    zip4(lo[0], lo[1], hi[0], hi[1], x); split(x, d0, rk0 & 1, a[0], a[1], w0, rs[0], rs[1]);
    zip4(lo[2], lo[3], hi[2], hi[3], x); split(x, d1, rk1 & 1, a[2], a[3], w1, rs[2], rs[3]);
    const int mt = rb >> 2, tid = (rb & 3) * 32 + lane;
    g_afrag[(mt * KSTEPS + ks) * 128 + tid] = make_uint4(a[0], a[1], a[2], a[3]);
    w0 <<= 4 * q; w1 <<= 4 * q;
    w0 |= __shfl_xor_sync(~0u, w0, 1); w1 |= __shfl_xor_sync(~0u, w1, 1);
    w0 |= __shfl_xor_sync(~0u, w0, 2); w1 |= __shfl_xor_sync(~0u, w1, 2);
    if ((q >> 1) == (ks & 1)) aux[((ks >> 3) * 32 + lane) * 4 + ((ks >> 1) & 3)] = (q & 1) ? w1 : w0;
    const int em = min(ne, max(8, 16 - no)), om = min(no, 16 - em);
    const int odd = q & 1, m = odd ? om : em;
    auto place = [&](int rk) {
        const int t = 15 - rk;
        return rk >= m ? 16 + (odd ? ne - em : 0) + rk - m : rk < 8 ? (rk >> 1) * 4 + 2 * odd + (rk & 1) : (t >> 1) * 4 + 2 * (odd ^ 1) + (t & 1);
    };
#pragma unroll
    for (int e = 0; e < 2; e++) {
        const int rk = e ? rk1 : rk0;
        const bool dbl = e ? d1 : d0;
        const uint32_t va = rs[2 * e], vb = rs[2 * e + 1];
        const uint32_t second = (__ballot_sync(~0u, vb != 0) & (0x11111111u << q)) != 0 && !dbl;
        if ((gm >> (4 * e + q)) & 1) {
            const int sl = place(rk);
            put_slot(sl >> 2, r * 4 + (sl & 3), !dbl ? va | vb : (rk & 1) ? vb : va, resid_off(g0 + 4 * e, rk & 1, r) | (second << 15));
            if (dbl) { const int s2 = place(rk + 1); put_slot(s2 >> 2, r * 4 + (s2 & 3), (rk & 1) ? va : vb, resid_off(g0 + 4 * e, ~rk & 1, r)); }
        }
    }
    const int ntot = ne + no;
    const int ng = ntot > 16 ? (ntot + 3) >> 2 : min(4, (max(ne, no) + 1) >> 1);
    if (ks == 7) { aux[(2 * 32 + lane) * 4 + 1] = ng | (units << 8); *(uint2*)(aux + (2 * 32 + lane) * 4 + 2) = bias2;
        aux[(3 * 32 + lane) * 4 + 3] = 0; *(uint2*)(aux + (5 * 32 + lane) * 4 + 2) = make_uint2(0, 0);
    }
    const int idx = 2 * ks + (q & 1);
    const int frow = ks < 6 ? ks : ks == 6 ? ng - 1 : ng;
    const bool fill = ks < 4 ? !(idx < ((q >> 1) ? om : em) || (15 - idx) < ((q >> 1) ? em : om))
                             : (ks < 6 || (ng > 6 && (ks == 6 || (ks == 8 && (ng & 1))))) && 4 * frow + q >= ntot;
    if (fill) put_slot(frow, lane, 0, resid_off(q >> 1, q & 1, r));
}

template<int SEL> __device__ __forceinline__ void wgmma_sp(float (&d)[NACC], const uint32_t (&a)[4], uint64_t bdesc, uint32_t meta) {
    asm volatile("{\n.reg .pred p;\nsetp.ne.b32 p, %22, 0;\n"
        "wgmma.mma_async.sp.sync.aligned.m64n32k32.f32.bf16.bf16 {%0, %1, %2, %3, %4, %5, %6, %7, %8, %9, %10, %11, %12, %13, %14, %15}, {%16, %17, %18, %19}, %20, %21, %23, p, 1, 1, 0;\n}\n"
        : "+f"(d[0]), "+f"(d[1]), "+f"(d[2]), "+f"(d[3]), "+f"(d[4]), "+f"(d[5]), "+f"(d[6]), "+f"(d[7]), "+f"(d[8]), "+f"(d[9]), "+f"(d[10]), "+f"(d[11]), "+f"(d[12]), "+f"(d[13]), "+f"(d[14]), "+f"(d[15])
        : "r"(a[0]), "r"(a[1]), "r"(a[2]), "r"(a[3]), "l"(bdesc), "r"(meta), "r"(1), "n"(SEL));
}

__device__ __forceinline__ void mbar_init(uint32_t bar, uint32_t cnt) { asm volatile("mbarrier.init.shared::cta.b64 [%0], %1;" :: "r"(bar), "r"(cnt) : "memory"); }
__device__ __forceinline__ void mbar_expect_tx(uint32_t bar, uint32_t bytes) {
    asm volatile("mbarrier.arrive.expect_tx.shared::cta.b64 _, [%0], %1;" :: "r"(bar), "r"(bytes) : "memory");
}
__device__ __forceinline__ void mbar_arrive(uint32_t bar) { asm volatile("mbarrier.arrive.shared::cta.b64 _, [%0];" :: "r"(bar) : "memory"); }
__device__ __forceinline__ void mbar_arrive_cluster(uint32_t bar) { asm volatile("mbarrier.arrive.shared::cluster.b64 _, [%0];" :: "r"(bar) : "memory"); }
__device__ __forceinline__ bool mbar_try(uint32_t bar, uint32_t parity) {
    uint32_t ok;
    asm volatile("{\n.reg .pred p;\nmbarrier.try_wait.parity.shared::cta.b64 p, [%1], %2;\nselp.u32 %0, 1, 0, p;\n}\n" : "=r"(ok) : "r"(bar), "r"(parity) : "memory");
    return ok;
}
__device__ __forceinline__ bool mbar_test(uint32_t bar, uint32_t parity) {
    uint32_t ok;
    asm volatile("{\n.reg .pred p;\nmbarrier.test_wait.parity.shared::cta.b64 p, [%1], %2;\nselp.u32 %0, 1, 0, p;\n}\n" : "=r"(ok) : "r"(bar), "r"(parity) : "memory");
    return ok;
}
__device__ __forceinline__ void fail_if(bool c) { asm volatile("{\n.reg .pred p;\nsetp.ne.u32 p, %0, 0;\n@p st.volatile.global.u32 [%1], %0;\n}\n" :: "r"((uint32_t)c), "l"(0ull) : "memory"); }
__device__ __forceinline__ void mbar_wait(uint32_t bar, uint32_t parity) {
    int n = 0;
    while (!mbar_try(bar, parity)) fail_if(++n > (1 << 20));
}
__device__ __forceinline__ void st_async(uint32_t addr, uint32_t v, uint32_t bar) {
    asm volatile("st.async.weak.shared::cluster.mbarrier::complete_tx::bytes.u32 [%0], %1, [%2];" :: "r"(addr), "r"(v), "r"(bar) : "memory");
}
__device__ __forceinline__ uint32_t mapa(uint32_t a, uint32_t cta) { uint32_t d; asm("mapa.shared::cluster.u32 %0, %1, %2;" : "=r"(d) : "r"(a), "r"(cta)); return d; }
__device__ __forceinline__ uint32_t lds32(uint32_t a) { uint32_t v; asm volatile("ld.shared.b32 %0, [%1];" : "=r"(v) : "r"(a)); return v; }
__device__ __forceinline__ uint32_t lds32v(uint32_t a) { uint32_t v; asm volatile("ld.volatile.shared.b32 %0, [%1];" : "=r"(v) : "r"(a) : "memory"); return v; }
__device__ __forceinline__ void sts32(uint32_t a, uint32_t v) { asm volatile("st.shared.b32 [%0], %1;" :: "r"(a), "r"(v) : "memory"); }
__device__ __forceinline__ uint4 ldw(const uint4* a) { uint4 v; asm volatile("ld.weak.global.L1::no_allocate.v4.u32 {%0,%1,%2,%3}, [%4];" : "=r"(v.x), "=r"(v.y), "=r"(v.z), "=r"(v.w) : "l"(a) : "memory"); return v; }
__device__ __forceinline__ void mma_k8(float* c, uint2 a, uint32_t b) {
    asm volatile("mma.sync.aligned.m16n8k8.row.col.f32.bf16.bf16.f32 {%0,%1,%2,%3}, {%4,%5}, {%6}, {%0,%1,%2,%3};"
                 : "+f"(c[0]), "+f"(c[1]), "+f"(c[2]), "+f"(c[3]) : "r"(a.x), "r"(a.y), "r"(b));
}
__device__ __forceinline__ void mma_k16(float* d, uint2 a, uint2 a2, uint32_t b0, uint32_t b1, float c0, float c1, float c2, float c3) {
    asm volatile("mma.sync.aligned.m16n8k16.row.col.f32.bf16.bf16.f32 {%0,%1,%2,%3}, {%4,%5,%6,%7}, {%8,%9}, {%10,%11,%12,%13};"
                 : "=f"(d[0]), "=f"(d[1]), "=f"(d[2]), "=f"(d[3]) : "r"(a.x), "r"(a.y), "r"(a2.x), "r"(a2.y), "r"(b0), "r"(b1), "f"(c0), "f"(c1), "f"(c2), "f"(c3));
}
__device__ __forceinline__ uint32_t pack_bias(float lo, float hi, uint32_t bias2) {
    uint32_t p, o;
    asm("cvt.rn.bf16x2.f32 %0, %1, %2;" : "=r"(p) : "f"(hi), "f"(lo));
    asm("add.rn.bf16x2 %0, %1, %2;" : "=r"(o) : "r"(p), "r"(bias2));
    return o;
}

struct Params {
    const uint16_t* w; const uint16_t* bias; const uint8_t* x;
    int nq, npages;
    int ncl, nh;
    int nctas;
    int tb, ta, te, slope0, slope1, c0;
    int m0;
    uint32_t ratio[8]; int rm[8];
};
struct Maps { CUtensorMap x[2], o[2], pf; };
__device__ __forceinline__ uint4 entry_w(int M, int w, int q, int extra) {
    const int r = M - (M >> 6), o = (r * 9363) >> 16, t = r - 7 * o, odd = t & 1, n = t >> 1;
    const int u = w ^ o ^ odd;
    const int C = 8 * o + 2 * n + ((n ^ u) & 1), C2 = 8 * o + 6 + ((1 ^ u) & 1);
    const uint32_t ra = 57 * C - ((C * 7282) >> 16) + 4 * odd, rb = odd ? 57 * C2 - ((C2 * 7282) >> 16) + 4 + 2 * n : ra + 12;
    const uint32_t rm = 2048 * (2 * (M >> 6) + w) + 56;
    const bool mixed = (M & 63) == 63;
    return make_uint4(M | (mixed << 14) | (q << 17) | (extra << 18), mixed ? rm * 0x10001u + (512u << 16) : ra * 0x10001u + (2u << 16),
                      mixed ? rm * 0x10001u + (1024u | 1536u << 16) : (ra + (odd ? 4 : 10)) | (rb << 16), 0);
}
__device__ __forceinline__ uint4 entry(int M, int q, int extra, unsigned long long plan) {
    const int r = M - (M >> 6), page = (r * 2341) >> 16;
    return entry_w(M, (M & 63) == 63 ? q : q ^ (int)((plan >> page) & 1), q, extra);
}
__device__ __forceinline__ int frontier(const Params& p, int t) {
    t = max(t, p.tb);
    const int l = t < p.ta ? LEAD0 + ((p.slope0 * (t - p.tb)) >> 16) : LEADE + max(0, (p.slope1 * (p.te - t)) >> 16);
    return (min(p.nq, t + l) * 9) >> 3;
}
__device__ __forceinline__ uint4 cl_entry(const Params& p, int m, int q, uint32_t ratio, unsigned long long plan) {
    const int nb = (m * ratio + 0x8000u) >> 16, nb1 = m ? ((m - 1) * ratio + 0x8000u) >> 16 : 0;
    uint4 e = entry(p.m0 + m + nb, q, nb - nb1, plan);
    const int c0 = frontier(p, p.m0 + m - 1 + nb1);
    e.w = c0 | (frontier(p, p.m0 + m + nb) - c0) << 16;
    return e;
}
__device__ __forceinline__ int helpers(const Params& p, unsigned long long plan, int q) {
    const int h0 = min(max(((p.ncl + p.nh) >> 1) - (p.ncl - (int)((plan >> 48) & 0xFF)), 0), p.nh);
    return q ? p.nh - h0 : h0;
}
__device__ __forceinline__ void draw(uint32_t& v, uint32_t* ctr, uint32_t inc) {
    asm volatile("{\n.reg .pred p;\nelect.sync _|p, 0xffffffff;\n@p atom.relaxed.gpu.global.add.u32 %0, [%1], %2;\n}" : "+r"(v) : "l"(ctr), "r"(inc) : "memory");
}
__device__ __forceinline__ uint4 lds128v(uint32_t a) { uint4 v; asm volatile("ld.volatile.shared.v4.b32 {%0,%1,%2,%3}, [%4];" : "=r"(v.x), "=r"(v.y), "=r"(v.z), "=r"(v.w) : "r"(a) : "memory"); return v; }
__device__ __forceinline__ void sts128(uint32_t a, uint4 e) { asm volatile("st.shared.v4.b32 [%0], {%1,%2,%3,%4};" :: "r"(a), "r"(e.x), "r"(e.y), "r"(e.z), "r"(e.w) : "memory"); }

__device__ __forceinline__ const uint8_t* probe_line(const Params& p, int page, int cell, int line, int parity) {
    return p.x + ((size_t)page << 21) + cell * 65536 + ((__popc(cell & 0xB) ^ parity) & 1) * 4096 + line * 128;
}
__device__ __forceinline__ int near_parity(const Params& p, int page, int cell, int line, uint32_t scratch, uint32_t since) {
    int sum = 0;
#pragma unroll 1
    for (int e = -1; e < NPR; e++) {
        uint32_t a = 0, b = 0, t0, t1;
        asm volatile("{\n.reg .pred p;\nsetp.ge.s32 p, %4, 0;\n@p ld.global.cg.u32 %0, [%2];\n@p ld.global.cg.u32 %1, [%3];\n}"
                     : "+r"(a), "+r"(b) : "l"(probe_line(p, page, cell, line + e, e & 1)), "l"(probe_line(p, page, cell, line + e, ~e & 1)), "r"(e) : "memory");
        asm volatile("st.volatile.shared.u32 [%0], %1;" :: "r"(scratch), "r"(a) : "memory");
        asm volatile("mov.u32 %0, %%clock;" : "=r"(t0) :: "memory");
        asm volatile("st.volatile.shared.u32 [%0], %1;" :: "r"(scratch), "r"(b) : "memory");
        asm volatile("mov.u32 %0, %%clock;" : "=r"(t1) :: "memory");
        const int d = min(t1 - t0, 200u);
        sum = e < 0 ? 0 : (e & 1) ? sum + d : sum - d;
        while (t1 - since < PWAIT) asm volatile("mov.u32 %0, %%clock;" : "=r"(t1) :: "memory");
    }
    return sum > 0;
}

template <bool HELPER>
__global__ void __launch_bounds__(NTHREADS, 1)
spgemm_kernel(const __grid_constant__ Maps maps, const __grid_constant__ Params p) {
    extern __shared__ unsigned char smem_raw[];
    const uint32_t sb = ((uint32_t)__cvta_generic_to_shared(smem_raw) + 1023u) & ~1023u;
    const int tid = threadIdx.x, warp = __shfl_sync(~0u, tid >> 5, 0), lane = tid & 31;
    const int rank = blockIdx.x % CL, cid = blockIdx.x / CL;
    const uint32_t bar_full = sb + OFF_FULL, bar_empty = sb + OFF_EMPTY, tk = sb + OFF_TK;
    uint4 wv[4];
    const int wrow = warp * 16 + (lane & 3) * 4;
    uint32_t b0, b1;
    auto prep_load = [&](int mtile) {
        b0 = __ldg(p.bias + mtile * 64 + lane); b1 = __ldg(p.bias + mtile * 64 + 32 + lane);
#pragma unroll
        for (int j = 0; j < 4; j++) wv[j] = __ldg((const uint4*)(p.w + (rank * 192 + wrow + j) * D + mtile * 64 + (lane >> 2) * 8));
    };
    if (!HELPER && warp < 12 && cid < 36) prep_load(cid >> 2);

    if (warp >= 12) {
        asm volatile("setmaxnreg.dec.sync.aligned.u32 32;");
        const int ppage = warp == 15 ? p.npages - 1 : cid, pcell = warp == 15 ? cid & 31 : 30, pline = warp == 15 ? (cid >> 5) * NPR : 2 * NPR;
        const bool prober = !HELPER && rank == 0 && (warp == 15 || (warp == 14 && cid < p.npages));
        uint32_t tp;
        asm volatile("mov.u32 %0, %%clock;" : "=r"(tp) :: "memory");
        if (prober && lane < 2 * NPR) asm volatile("prefetch.global.L2 [%0];" :: "l"(probe_line(p, ppage, pcell, pline + (lane >> 1), lane & 1)) : "memory");
        if (tid == NCONS) {
#pragma unroll
            for (int s = 0; s < NSLOT; s++) { mbar_init(bar_full + 8 * s, 1); mbar_init(bar_empty + 8 * s, HELPER ? 3 : 3 * CL); }
#pragma unroll
            for (int j = 0; j < 8; j++) sts32(tk + 16 * j, 0);
            mbar_init(sb + OFF_MBAR, 1); mbar_init(sb + OFF_MBAR + 8, 1);
            mbar_init(sb + OFF_GO, HELPER ? 12 : 12 + CL); mbar_init(sb + OFF_PLAN, 1); mbar_init(sb + OFF_PLAN2, 1);
            asm volatile("fence.mbarrier_init.release.cluster;" ::: "memory");
            mbar_expect_tx(sb + OFF_MBAR, 36 * 8);
            if (!HELPER && rank != 0) mbar_expect_tx(sb + OFF_PLAN, 16);
            if (!HELPER) asm volatile("griddepcontrol.launch_dependents;");
#pragma unroll
            for (int j = 0; j < 2; j++) { asm volatile("prefetch.tensormap [%0];" :: "l"(&maps.x[j]) : "memory"); asm volatile("prefetch.tensormap [%0];" :: "l"(&maps.o[j]) : "memory"); }
            asm volatile("prefetch.tensormap [%0];" :: "l"(&maps.pf) : "memory");
        }
        __syncwarp();
        auto wait_plan = [&]() -> unsigned long long {
            unsigned long long v; int n = 0;
            do { asm volatile("ld.relaxed.gpu.global.u64 %0, [%1];" : "=l"(v) : "l"(&g_plan) : "memory"); fail_if(++n > (1 << 22)); } while (__any_sync(~0u, (int)((v >> 40) & 0xFF) != p.ncl));
            return v;
        };
        if (HELPER) {
            asm volatile("bar.sync 0;" ::: "memory");
            if (warp == 15) {
                const unsigned long long plan = wait_plan();
                int idx = cid, nh = helpers(p, plan, 0), q = 2 * nh < p.nh;
                if (q) nh = p.nh - nh;
                if (idx >= nh) { idx -= nh; nh = p.nh - nh; q ^= 1; }
                const uint32_t ratio = p.ratio[nh];
                const int rm = p.rm[nh], H = p.nq - p.m0 - rm;
                for (int j0 = 0; __any_sync(~0u, idx + (j0 - 1) * nh < H); j0 += 32) {
                    const int k = idx + (j0 + lane) * nh, mk = (((k + 1) << 16) - 0x8000u + ratio - 1) / ratio;
                    uint4 e = entry(p.m0 + min(mk, rm) + k, q, 0, plan);
                    if (k >= H) e.x = NO_TILE;
                    sts128(sb + OFF_TAB + 16 * (j0 + lane), e);
                }
                __syncwarp();
                if (lane == 0) mbar_arrive(sb + OFF_PLAN);
            }
        } else {
            asm volatile("barrier.cluster.arrive.relaxed.aligned;" ::: "memory");
            int side = 0;
            if (prober) side = near_parity(p, ppage, pcell, pline, sb + OFF_INFO + 16 + 4 * (warp & 1), tp);
            if (warp == 14 && lane == 0) sts32(sb + OFF_INFO + 24, side);
            asm volatile("barrier.cluster.wait.aligned;" ::: "memory");
            if (rank == 0 && warp >= 14) asm volatile("bar.sync 11, 64;" ::: "memory");
            if (warp >= 13) {
                if (warp == 15 && rank == 0) {
                    unsigned long long old = 0;
                    const unsigned long long mine = cid < p.npages ? (unsigned long long)(lds32v(sb + OFF_INFO + 24) ^ side) << cid : 0ull;
                    if (lane == 0) old = atomicAdd(&g_plan, mine + (1ull << 40) + ((unsigned long long)side << 48));
                    const uint32_t oh = __shfl_sync(~0u, (uint32_t)(old >> 32), 0);
                    const unsigned long long v = wait_plan();
                    const int n1 = (oh >> 16) & 0xFF, n = (oh >> 8) & 0xFF, t1 = (int)(v >> 48) & 0xFF;
                    const uint4 inf = make_uint4((uint32_t)v, (uint32_t)(v >> 32), side | (side ? n1 : n - n1) << 8 | (side ? t1 : p.ncl - t1) << 16, 0);
                    if (lane == 0) sts128(sb + OFF_INFO, inf);
                    else if (lane < CL)
                        asm volatile("st.async.weak.shared::cluster.mbarrier::complete_tx::bytes.v4.u32 [%0], {%1, %2, %3, %4}, [%5];"
                                     :: "r"(mapa(sb + OFF_INFO, lane)), "r"(inf.x), "r"(inf.y), "r"(inf.z), "r"(inf.w), "r"(mapa(sb + OFF_PLAN, lane)) : "memory");
                }
                if (rank == 0) asm volatile("bar.sync 15, 96;" ::: "memory"); else mbar_wait(sb + OFF_PLAN, 0);
                const uint4 inf = lds128v(sb + OFF_INFO);
                const unsigned long long plan = inf.x | ((unsigned long long)inf.y << 32);
                const int nh = helpers(p, plan, inf.z & 1), rm = p.rm[nh], nc = inf.z >> 16;
                const uint32_t ratio = p.ratio[nh];
                if (warp == 15 && rank == 0) {
                    const int m = ((inf.z >> 8) & 0xFF) + min(lane, NSTAT - 1) * nc;
                    sts128(sb + OFF_TAB + 16 * m, cl_entry(p, m, inf.z & 1, ratio, plan));
                    __syncwarp();
                    if (lane == 0) { mbar_arrive(sb + OFF_PLAN); mbar_expect_tx(sb + OFF_PLAN2, 16 * (rm - NSTAT * nc)); }
                }
                const uint32_t rtab = mapa(sb + OFF_TAB, 0), rbar = mapa(sb + OFF_PLAN2, 0);
                for (int m0 = NSTAT * nc + 96 * (2 - rank); __any_sync(~0u, m0 < rm); m0 += 288) {
                    const int m = m0 + tid - (NCONS + 32);
                    const uint4 e = cl_entry(p, m, inf.z & 1, ratio, plan);
                    if (m < rm) asm volatile("st.async.weak.shared::cluster.mbarrier::complete_tx::bytes.v4.u32 [%0], {%1, %2, %3, %4}, [%5];"
                                             :: "r"(rtab + 16 * m), "r"(e.x), "r"(e.y), "r"(e.z), "r"(e.w), "r"(rbar) : "memory");
                }
            }
        }
        if (warp == 12) {
            if (!HELPER && rank != 0) {
                mbar_wait(sb + OFF_PLAN, 0);
                const uint4 inf = lds128v(sb + OFF_INFO);
                const unsigned long long plan = inf.x | ((unsigned long long)inf.y << 32);
                auto cell = [&](int c, int q) {
                    const int y = 32 * c - 2 + 4 * ((__popc(c & 0xB) ^ (int)(plan >> (c >> 5)) ^ q) & 1);
                    asm volatile("{\n.reg .pred p;\nelect.sync _|p, 0xffffffff;\n@p cp.async.bulk.prefetch.tensor.3d.L2.global.tile [%0, {%1, %2, %1}];\n}" :: "l"(&maps.pf), "r"(0), "r"(y) : "memory");
                };
                const int fe0 = frontier(p, 0), step = 2 * (inf.z >> 16);
                int u0 = p.c0 + 2 * ((inf.z >> 8) & 0xFF) + rank - 1;
                {
                    uint32_t t, due;
                    asm volatile("mov.u32 %0, %%clock;" : "=r"(due) :: "memory");
                    due += (PACE * (u0 - p.c0)) / step;
                    for (; __any_sync(~0u, u0 < fe0); u0 += step, due += PACE) {
                        do { asm volatile("mov.u32 %0, %%clock;" : "=r"(t) :: "memory"); } while (__any_sync(~0u, (int)(t - due) < 0));
                        cell(u0, inf.z & 1);
                    }
                }
                for (int j = XEARLY + rank - 1;; j += 2) {
                    uint4 v; uint32_t ahead;
                    for (int n = 0; __any_sync(~0u, (ahead = (((v = lds128v(tk + ((j & 7) << 4))).x >> 20) - (j + 1)) & 0xFFF) >= 0x800); n++) {
                        if (__any_sync(~0u, lds32v(tk + (((j - 1) & 7) << 4)) == (NO_TILE | (uint32_t)j << 20))) { v.x = NO_TILE; break; }
                        __nanosleep(100); fail_if(n > (1 << 24));
                    }
                    if (__any_sync(~0u, (v.x & NO_TILE) == NO_TILE)) break;
                    j += __reduce_max_sync(~0u, ahead);
                    for (int u = v.w & 0xFFFF; __any_sync(~0u, u < (v.w & 0xFFFF) + (v.w >> 16)); u++) cell(u, (v.x >> 17) & 1);
                }
            } else {
                const uint32_t rtk = HELPER ? tk : mapa(tk, lane < CL ? lane : 0), rfull = HELPER ? bar_full : mapa(bar_full, lane < CL ? lane : 0);
                int s = 0; uint32_t ph = 1;
                uint64_t pol;
                if (!HELPER) asm volatile("createpolicy.fractional.L2::evict_first.b64 %0, 1.0;" : "=l"(pol));
                else asm volatile("createpolicy.fractional.L2::evict_normal.b64 %0, 1.0;" : "=l"(pol));
                auto request = [&](int j, const uint4& t) {
                    const bool valid = t.x != NO_TILE;
                    const CUtensorMap* tm = &maps.x[(t.x >> 14) & 1];
                    mbar_wait(bar_empty + 8 * s, ph);
                    if (__any_sync(~0u, valid)) {
                        const uint32_t dst = sb + OFF_X + s * TILE_BYTES;
                        if (HELPER)
                            asm volatile("{\n.reg .pred p;\nelect.sync _|p, 0xffffffff;\n"
                                         "@p cp.async.bulk.tensor.4d.shared::cluster.global.mbarrier::complete_tx::bytes.L2::cache_hint [%0], [%4, {%6, %7, %6, %6}], [%5], %11;\n"
                                         "@p cp.async.bulk.tensor.4d.shared::cluster.global.mbarrier::complete_tx::bytes.L2::cache_hint [%1], [%4, {%6, %8, %6, %6}], [%5], %11;\n"
                                         "@p cp.async.bulk.tensor.4d.shared::cluster.global.mbarrier::complete_tx::bytes.L2::cache_hint [%2], [%4, {%6, %9, %6, %6}], [%5], %11;\n"
                                         "@p cp.async.bulk.tensor.4d.shared::cluster.global.mbarrier::complete_tx::bytes.L2::cache_hint [%3], [%4, {%6, %10, %6, %6}], [%5], %11;\n}\n"
                                         :: "r"(dst), "r"(dst + 9216), "r"(dst + 2 * 9216), "r"(dst + 3 * 9216), "l"(tm), "r"(bar_full + 8 * s), "r"(0),
                                            "r"(t.y & 0xFFFF), "r"(t.y >> 16), "r"(t.z & 0xFFFF), "r"(t.z >> 16), "l"(pol) : "memory");
                        else
                            asm volatile("{\n.reg .pred p;\nelect.sync _|p, 0xffffffff;\n"
                                         "@p cp.async.bulk.tensor.4d.shared::cluster.global.mbarrier::complete_tx::bytes.multicast::cluster.L2::cache_hint [%0], [%4, {%6, %7, %6, %6}], [%5], %11, %12;\n"
                                         "@p cp.async.bulk.tensor.4d.shared::cluster.global.mbarrier::complete_tx::bytes.multicast::cluster.L2::cache_hint [%1], [%4, {%6, %8, %6, %6}], [%5], %11, %12;\n"
                                         "@p cp.async.bulk.tensor.4d.shared::cluster.global.mbarrier::complete_tx::bytes.multicast::cluster.L2::cache_hint [%2], [%4, {%6, %9, %6, %6}], [%5], %11, %12;\n"
                                         "@p cp.async.bulk.tensor.4d.shared::cluster.global.mbarrier::complete_tx::bytes.multicast::cluster.L2::cache_hint [%3], [%4, {%6, %10, %6, %6}], [%5], %11, %12;\n}\n"
                                         :: "r"(dst), "r"(dst + 9216), "r"(dst + 2 * 9216), "r"(dst + 3 * 9216), "l"(tm), "r"(bar_full + 8 * s), "r"(0),
                                            "r"(t.y & 0xFFFF), "r"(t.y >> 16), "r"(t.z & 0xFFFF), "r"(t.z >> 16), "h"((uint16_t)((1u << CL) - 1)), "l"(pol) : "memory");
                    }
                    if (HELPER) {
                        if (lane == 0) { sts128(tk + ((j & 7) << 4), t); mbar_expect_tx(bar_full + 8 * s, valid ? TILE_BYTES : 0); }
                    } else if (lane < CL) {
                        asm volatile("mbarrier.arrive.expect_tx.shared::cluster.b64 _, [%0], %1;" :: "r"(rfull + 8 * s), "r"(valid ? TILE_BYTES + 16 : 16) : "memory");
                        asm volatile("st.async.weak.shared::cluster.mbarrier::complete_tx::bytes.v4.u32 [%0], {%1, %2, %3, %4}, [%5];"
                                     :: "r"(rtk + ((j & 7) << 4)), "r"(t.x | ((uint32_t)(j + 1) << 20)), "r"(t.y), "r"(t.z), "r"(t.w), "r"(rfull + 8 * s) : "memory");
                    }
                    if (++s == NSLOT) { s = 0; ph ^= 1; }
                };
                if (HELPER) {
#pragma unroll 1
                    for (int j = 0; j < XEARLY; j++) request(j, entry_w(p.ncl + cid + (j >> 1) * (p.ncl + p.nh), j & 1, j & 1, 0));
                    mbar_wait(sb + OFF_PLAN, 0);
                    mbar_wait(sb + OFF_GO, 0);
                    for (int j = XEARLY;; j++) {
                        const uint4 t = lds128v(sb + OFF_TAB + 16 * (j - XEARLY));
                        request(j, t);
                        if (__any_sync(~0u, t.x == NO_TILE)) break;
                    }
                } else {
#pragma unroll 1
                    for (int j = 0; j < XEARLY; j++) request(j, entry_w(cid + (j >> 1) * (p.ncl + p.nh), j & 1, j & 1, 0));
                    mbar_wait(sb + OFF_PLAN, 0);
                    const uint4 inf = lds128v(sb + OFF_INFO);
                    const unsigned long long plan = inf.x | ((unsigned long long)inf.y << 32);
                    const int side = inf.z & 1, nc = inf.z >> 16;
                    const int nh = helpers(p, plan, side), rm = p.rm[nh], rmo = p.rm[p.nh - nh];
                    const uint32_t ratio = p.ratio[nh], ratioo = p.ratio[p.nh - nh];
                    const int st = NSTAT * nc, sto = NSTAT * (p.ncl - nc);
                    uint4 t = lds128v(sb + OFF_TAB + 16 * ((inf.z >> 8) & 0xFF));
                    mbar_wait(sb + OFF_GO, 0);
                    int j = XEARLY;
#pragma unroll 1
                    for (; j < XEARLY + NSTAT - 2; j++) {
                        const uint4 tn = lds128v(sb + OFF_TAB + 16 * (((inf.z >> 8) & 0xFF) + (j + 1 - XEARLY) * nc));
                        request(j, t);
                        t = tn;
                    }
                    uint32_t drawn = 0;
                    int q = side;
                    {
                        draw(drawn, &g_ticket, 1u << (16 * side));
                        const uint4 tn = lds128v(sb + OFF_TAB + 16 * (((inf.z >> 8) & 0xFF) + (NSTAT - 1) * nc));
                        request(j++, t);
                        t = tn;
                        mbar_wait(sb + OFF_PLAN2, 0);
                    }
                    for (;; j++) {
                        uint32_t v = __reduce_max_sync(~0u, drawn);
                        int m = st + ((v >> (16 * side)) & 0xFFFF), mo = sto + ((v >> (16 - 16 * side)) & 0xFFFF);
                        if (q == side ? m >= rm && mo < rmo : mo >= rmo && m < rm) {
                            q ^= 1;
                            draw(drawn, &g_ticket, 1u << (16 * q));
                            v = __reduce_max_sync(~0u, drawn);
                            m = st + ((v >> (16 * side)) & 0xFFFF); mo = sto + ((v >> (16 - 16 * side)) & 0xFFFF);
                        }
                        uint4 tn;
                        const bool last = q == side ? m >= rm : mo >= rmo;
                        if (q == side) tn = lds128v(sb + OFF_TAB + 16 * min(m, NTAB - 1));
                        else tn = cl_entry(p, mo, q, ratioo, plan);
                        if (last) tn.x = NO_TILE;
                        q = m + ((m * ratio) >> 16) > mo + ((mo * ratioo) >> 16) + DELTA ? side ^ 1 : side;
                        if (!last) draw(drawn, &g_ticket, 1u << (16 * q));
                        request(j, t);
                        t = tn;
                        if (last) break;
                    }
                    request(j + 1, t);
                    if (lane == 0 && atomicInc(&g_done, p.ncl - 1) == (uint32_t)p.ncl - 1) g_ticket = 0;
                }
            }
        } else {
            const int g = warp - 13;
            uint64_t spol;
            asm volatile("createpolicy.fractional.L2::evict_first.b64 %0, 1.0;" : "=l"(spol));
            mbar_wait(sb + OFF_GO, 0);
            if (g == 2 && lane == 0 && atomicInc(&g_passed, p.nctas - 1) == (uint32_t)p.nctas - 1) {
#pragma unroll
                for (int m = 0; m < 9; m++) g_ready[m * 32] = 0;
                g_plan = 0;
            }
            __syncwarp();
            for (int i = 0;; i++) {
                asm volatile("bar.arrive %0, 160;" :: "r"(12 + g) : "memory");
                asm volatile("bar.sync %0, 160;" :: "r"(1 + g) : "memory");
                const uint4 t = lds128v(tk + ((i & 7) << 4));
                if ((t.x & NO_TILE) == NO_TILE) break;
                const CUtensorMap* tm = &maps.o[(t.x >> 14) & 1];
                const int row[4] = {(int)(t.y & 0xFFFF), (int)(t.y >> 16), (int)(t.z & 0xFFFF), (int)(t.z >> 16)};
                if (lane == 0) {
#pragma unroll
                    for (int k = 0; k < 4; k++)
                        asm volatile("cp.async.bulk.tensor.3d.global.shared::cta.bulk_group.L2::cache_hint [%0, {%2, %3, %4}], [%1], %5;"
                                     :: "l"(tm), "r"(sb + OFF_STG + g * STG_BYTES + k * 1024), "r"((g * 3 + rank) * 64), "r"(row[k]), "r"(0), "l"(spol) : "memory");
                    asm volatile("cp.async.bulk.commit_group;" ::: "memory");
                    asm volatile("cp.async.bulk.wait_group.read 0;" ::: "memory");
                }
                __syncwarp();
            }
        }
        __syncwarp();
        if (!HELPER) asm volatile("barrier.cluster.arrive.relaxed.aligned;\nbarrier.cluster.wait.aligned;" ::: "memory");
    } else {
        asm volatile("setmaxnreg.inc.sync.aligned.u32 160;");
        const int wg = warp >> 2, wtid = tid & 127, r = lane >> 2;
        if (HELPER) asm volatile("bar.sync 0;" ::: "memory");
        else {
            int prb = cid;
            asm volatile("barrier.cluster.arrive.relaxed.aligned;" ::: "memory");
            if (prb >= 36) asm volatile("barrier.cluster.wait.aligned;" ::: "memory");
#pragma unroll 1
            for (int round = 0; prb < 36; prb += p.ncl, round++) {
                const uint32_t wsm = sb + OFF_WST, msk = sb + OFF_MSK + (round & 1) * 288, mbar = sb + OFF_MBAR + (round & 1) * 8;
                if (round) {
                    asm volatile("bar.sync 3, 384;" ::: "memory");
                    if (tid == 0) mbar_expect_tx(mbar, 36 * 8);
                    prep_load(prb >> 2);
                }
                const int nt = ties(wv[0].x, wv[1].x, wv[2].x, wv[3].x) + ties(wv[0].y, wv[1].y, wv[2].y, wv[3].y) +
                               ties(wv[0].z, wv[1].z, wv[2].z, wv[3].z) + ties(wv[0].w, wv[1].w, wv[2].w, wv[3].w);
                const uint32_t mk = __ballot_sync(~0u, nt > 0), md = __ballot_sync(~0u, nt > 1);
                if (round == 0) asm volatile("barrier.cluster.wait.aligned;" ::: "memory");
                if (lane < CL)
                    asm volatile("st.async.weak.shared::cluster.mbarrier::complete_tx::bytes.v2.u32 [%0], {%1, %2}, [%3];"
                                 :: "r"(mapa(msk + (rank * 12 + warp) * 8, lane)), "r"(mk), "r"(md), "r"(mapa(mbar, lane)) : "memory");
#pragma unroll
                for (int j = 0; j < 4; j++) {
                    const int row = wrow + j;
                    const uint32_t ad = wsm + row * 128 + (((lane >> 2) ^ ((row & 1) | ((row >> 1) & 6))) << 4);
                    asm volatile("st.shared.v4.b32 [%0], {%1,%2,%3,%4};" :: "r"(ad), "r"(wv[j].x), "r"(wv[j].y), "r"(wv[j].z), "r"(wv[j].w) : "memory");
                }
                if (warp >= 6) asm volatile("bar.arrive 1, 384;" ::: "memory");
                else {
                    asm volatile("bar.sync 1, 384;" ::: "memory");
                    mbar_wait(mbar, (round >> 1) & 1);
                    uint4 ms = make_uint4(0, 0, 0, 0);
                    if (lane < KSTEPS) ms = lds128v(msk + 16 * lane);
                    const uint32_t m0 = ms.x, m1 = ms.z;
                    uint32_t c0 = m0 - ((m0 >> 1) & 0x55555555u), c1 = m1 - ((m1 >> 1) & 0x55555555u);
                    c0 = (c0 & 0x33333333u) + ((c0 >> 2) & 0x33333333u) + (c1 & 0x33333333u) + ((c1 >> 2) & 0x33333333u);
                    c1 = __reduce_add_sync(~0u, (c0 >> 4) & 0x0F0F0F0Fu); c0 = __reduce_add_sync(~0u, c0 & 0x0F0F0F0Fu);
                    auto key = [&](int v) { return ((((v & 1) ? c1 : c0) >> (4 * (v & 6))) & 0xFFu) * 8 + v; };
                    const uint32_t ku = key(lane & 7);
                    int rk = (key(2 * (lane >> 3)) < ku) + (key(2 * (lane >> 3) + 1) < ku);
                    rk += __shfl_xor_sync(~0u, rk, 8); rk += __shfl_xor_sync(~0u, rk, 16);
                    const int pp = prb & 3;
                    const int ulo = __ffs(__ballot_sync(~0u, rk == pp)) - 1, uhi = __ffs(__ballot_sync(~0u, rk == 7 - pp)) - 1;
                    uint32_t lo[4], hi[4];
                    load_unit(wsm, warp, ulo, lane, lo); load_unit(wsm, warp, uhi, lane, hi);
                    auto bits = [&](uint32_t a, uint32_t b, int u) { return ((a >> (4 * u)) & 15u) | (((b >> (4 * u)) & 15u) << 4); };
                    const uint32_t tl = bits(m0, m1, ulo), th = bits(m0, m1, uhi);
                    const uint2 bias2 = make_uint2(__shfl_sync(~0u, ulo < 4 ? b0 : b1, (ulo * 8 + r) & 31) * 0x10001u, __shfl_sync(~0u, uhi < 4 ? b0 : b1, (uhi * 8 + r) & 31) * 0x10001u);
                    emit_step(lo, hi, tl | th, (tl & th) | bits(ms.y, ms.w, ulo) | bits(ms.y, ms.w, uhi), prb, rank * 6 + warp, lane, ulo | (uhi << 4), bias2);
                    asm volatile("bar.sync 2, 192;" ::: "memory");
                    if (tid == 0) asm volatile("red.release.gpu.global.add.u32 [%0], 1;" :: "l"(&g_ready[(prb >> 2) * 32]) : "memory");
                }
            }
            if (warp == 0 && lane < CL) mbar_arrive_cluster(mapa(sb + OFF_GO, lane));
        }
        const int mt = wg * 3 + rank, rb = mt * 4 + (warp & 3);
        if ((warp & 3) == 0) {
            uint32_t v; int n = 0;
            do { asm volatile("ld.acquire.gpu.global.u32 %0, [%1];" : "=r"(v) : "l"(&g_ready[mt * 32]) : "memory"); fail_if(++n > (1 << 22)); } while (__any_sync(~0u, v < 4 * CL));
        }
        asm volatile("bar.sync %0, 128;" :: "r"(12 + wg) : "memory");
        uint32_t a[KSTEPS][4], meta[9];
        uint2 rv[3]; uint32_t ro[3], sel[3];
        uint32_t info, bias_lo, bias_hi;
        {
            const uint4* ap = g_aux + rb * 6 * 32 + lane;
            const uint4 v3 = ldw(ap + 96), v2 = ldw(ap + 64), v4 = ldw(ap + 128), v5 = ldw(ap + 160), v0 = ldw(ap), v1 = ldw(ap + 32);
            meta[0] = v0.x; meta[1] = v0.y; meta[2] = v0.z; meta[3] = v0.w; meta[4] = v1.x; meta[5] = v1.y; meta[6] = v1.z; meta[7] = v1.w;
            meta[8] = v2.x; info = v2.y; bias_lo = v2.z; bias_hi = v2.w;
            ro[0] = v3.x; ro[1] = v3.y; ro[2] = v3.z;
            rv[0] = make_uint2(v4.x, v4.y); rv[1] = make_uint2(v4.z, v4.w); rv[2] = make_uint2(v5.x, v5.y);
        }
#pragma unroll
        for (int k = 0; k < KSTEPS; k++) { uint4 v = ldw(&g_afrag[(mt * KSTEPS + k) * 128 + wtid]); a[k][0] = v.x; a[k][1] = v.y; a[k][2] = v.z; a[k][3] = v.w; }
        if (lane == 0) mbar_arrive(sb + OFF_GO);
        auto selector = [](uint32_t o) { return 0x5410u + ((o >> 15) & 1) * 0x22u + (o >> 31) * 0x2200u; };
#pragma unroll
        for (int j = 0; j < 3; j++) { sel[j] = selector(ro[j]); ro[j] &= 0x7FFF7FFFu; }
        mbar_wait(bar_full, 0);
        info = __shfl_sync(~0u, info, 0);
        const int ngrp = info & 0xFF, ulo = (info >> 8) & 7, uhi = (info >> 12) & 7;
        const uint32_t stg = sb + OFF_STG + wg * STG_BYTES + ((lane >> 4) * 8 + (lane & 7)) * 128 + (((((lane >> 3) & 1) ? uhi : ulo) ^ (lane & 7)) << 4);
        const uint32_t rempty = HELPER ? bar_empty : mapa(bar_empty, 0);
        float acc[NACC];
        uint32_t bq[NB][6];
        auto gather = [&](uint32_t xb) {
#pragma unroll
            for (int j = 0; j < 4; j++) {
                const uint32_t o = xb + ((j & 1) ? ro[j >> 1] >> 16 : ro[j >> 1] & 0xFFFF);
#pragma unroll
                for (int n = 0; n < NB; n++) {
                    bq[n][j] = 0;
                    asm volatile("{\n.reg .pred p;\nsetp.lt.s32 p, %2, %3;\n@p ld.shared.b32 %0, [%1];\n}" : "+r"(bq[n][j]) : "r"(o + n * 9216), "r"(j), "r"(ngrp) : "memory");
                }
            }
#pragma unroll 1
            for (int z = 4; z < min(ngrp, 5); z++) {
#pragma unroll
                for (int n = 0; n < NB; n++) { bq[n][4] = lds32(xb + (ro[2] & 0xFFFF) + n * 9216); bq[n][5] = lds32(xb + (ro[2] >> 16) + n * 9216); }
            }
        };
        auto select = [&]() {
#pragma unroll
            for (int n = 0; n < NB; n++)
#pragma unroll
                for (int j = 0; j < 2; j++) bq[n][2 * j] = __byte_perm(bq[n][2 * j], bq[n][2 * j + 1], sel[j]);
        };
        auto further = [&](uint32_t xb, int bar) {
#pragma unroll 1
            for (int y = 4; y < min(ngrp, 5); y++) {
#pragma unroll
                for (int n = 0; n < NB; n++) mma_k8(acc + 4 * n, rv[2], __byte_perm(bq[n][4], bq[n][5], sel[2]));
                if (bar >= 0) asm volatile("bar.arrive %0, 256;" :: "r"(bar) : "memory");
#pragma unroll 1
                for (int z = 3; 2 * z < ngrp; z++) {
                    const uint2 v = __ldca(&g_rval[(rb * 36 + z) * 32 + lane]); const uint32_t off = __ldca(&g_roff[(rb * 36 + z) * 32 + lane]);
                    uint32_t bx[NB];
#pragma unroll
                    for (int n = 0; n < NB; n++) bx[n] = __byte_perm(lds32(xb + (off & 0x7FFF) + n * 9216), lds32(xb + ((off >> 16) & 0x7FFF) + n * 9216), selector(off));
#pragma unroll
                    for (int n = 0; n < NB; n++) mma_k8(acc + 4 * n, v, bx[n]);
                }
            }
        };
        bool more = true;
#pragma unroll
        for (int n = 0; n < NB; n++) bq[n][4] = bq[n][5] = 0;
        gather(sb + OFF_X);
        select();
#pragma unroll
        for (int n = 0; n < NB; n++) mma_k16(acc + 4 * n, rv[0], rv[1], bq[n][0], bq[n][2], 0.f, 0.f, 0.f, 0.f);
        further(sb + OFF_X, -1);
        const int bar_a = 8 + wg, bar_an = 8 + (wg + 2) % 3, bar_tn = 4 + (wg + 2) % 3;
        if (wg == 1) asm volatile("bar.arrive 4, 256;" ::: "memory");
        if (wg == 2) { asm volatile("bar.sync 10, 256;" ::: "memory"); asm volatile("bar.arrive 5, 256;" ::: "memory"); }
        int s = 0; uint32_t ph = 0;
        bool ready = false;
        for (int i = 0; more; i++) {
            const uint32_t xb = sb + OFF_X + s * TILE_BYTES;
            const int s1 = s + 1 == NSLOT ? 0 : s + 1;
            const uint32_t ph1 = s1 == 0 ? ph ^ 1 : ph;
            asm volatile("bar.sync %0, 256;" :: "r"(4 + wg) : "memory");
            const uint64_t desc = ((uint64_t)1 << 62) | ((uint64_t)(9216 >> 4) << 32) | ((uint64_t)1 << 16) | (uint64_t)(xb >> 4);
            asm volatile("wgmma.fence.sync.aligned;" ::: "memory");
#pragma unroll
            for (int k = 0; k < KSTEPS; k++) {
                const uint64_t d = desc + (uint64_t)(((k >> 1) * 1024 + (k & 1) * 64) >> 4);
                if (k & 1) wgmma_sp<1>(acc, a[k], d, meta[k >> 1]);
                else       wgmma_sp<0>(acc, a[k], d, meta[k >> 1]);
            }
            asm volatile("wgmma.commit_group.sync.aligned;" ::: "memory");
            asm volatile("bar.arrive %0, 256;" :: "r"(bar_an) : "memory");
            if (!ready) mbar_wait(bar_full + 8 * s1, ph1);
            const uint32_t tn = lds32v(tk + (((i + 1) & 7) << 4));
            gather(sb + OFF_X + s1 * TILE_BYTES);
            asm volatile("bar.sync %0, 160;" :: "r"(12 + wg) : "memory");
            asm volatile("wgmma.wait_group.sync.aligned 0;" ::: "memory");
            if (wtid == 0) { if (HELPER) mbar_arrive(bar_empty + 8 * s); else mbar_arrive_cluster(rempty + 8 * s); }
#pragma unroll
            for (int n = 0; n < NB; n += 2) {
                const uint32_t p0 = pack_bias(acc[4 * n], acc[4 * n + 1], bias_lo), p1 = pack_bias(acc[4 * n + 2], acc[4 * n + 3], bias_hi);
                const uint32_t p2 = pack_bias(acc[4 * n + 4], acc[4 * n + 5], bias_lo), p3 = pack_bias(acc[4 * n + 6], acc[4 * n + 7], bias_hi);
                if (n == 0) asm volatile("stmatrix.sync.aligned.m8n8.x4.trans.shared.b16 [%0], {%1,%2,%3,%4};" :: "r"(stg + n * 1024), "r"(p0), "r"(p1), "r"(p2), "r"(p3) : "memory");
                else asm volatile("{\n.reg .pred p;\nAGAIN:\nstmatrix.sync.aligned.m8n8.x4.trans.shared.b16 [%0], {%1,%2,%3,%4};\nsetp.eq.u32 p, %5, 0xFFFFFFFE;\n@p bra.uni AGAIN;\n}"
                                  :: "r"(stg + n * 1024), "r"(p0), "r"(p1), "r"(p2), "r"(p3), "r"(info) : "memory");
            }
            more = __any_sync(~0u, (tn & NO_TILE) != NO_TILE);
            select();
            if (wg != 2 || more) {
                asm volatile("{\n.reg .pred p;\nTURN:\nbar.sync %0, 256;\nsetp.eq.u32 p, %1, 0xFFFFFFFF;\n@p bra.uni TURN;\n}" :: "r"(bar_a), "r"(info) : "memory");
#pragma unroll
                for (int n = 0; n < NB; n++) {
                    mma_k16(acc + 4 * n, rv[0], rv[1], bq[n][0], bq[n][2], 0.f, 0.f, 0.f, 0.f);
                    if (n == 0) asm volatile("{\n.reg .pred p;\nsetp.le.s32 p, %1, 4;\n@p bar.arrive %0, 256;\n}" :: "r"(bar_tn), "r"(ngrp) : "memory");
                }
                further(sb + OFF_X + s1 * TILE_BYTES, bar_tn);
            }
            asm volatile("fence.proxy.async.shared::cta;" ::: "memory");
            asm volatile("bar.arrive %0, 160;" :: "r"(1 + wg) : "memory");
            s = s1; ph = ph1;
            ready = __all_sync(~0u, mbar_test(bar_full + 8 * (s + 1 == NSLOT ? 0 : s + 1), s + 1 == NSLOT ? ph ^ 1 : ph));
        }
        if (wg == 0) asm volatile("bar.sync 4, 256;" ::: "memory");
        asm volatile("bar.sync %0, 160;" :: "r"(12 + wg) : "memory");
        asm volatile("bar.arrive %0, 160;" :: "r"(1 + wg) : "memory");
        if (!HELPER) asm volatile("barrier.cluster.arrive.relaxed.aligned;\nbarrier.cluster.wait.aligned;" ::: "memory");
    }
}

typedef CUresult (*EncodeFn)(CUtensorMap*, CUtensorMapDataType, cuuint32_t, void*, const cuuint64_t*, const cuuint64_t*, const cuuint32_t*, const cuuint32_t*,
                             CUtensorMapInterleave, CUtensorMapSwizzle, CUtensorMapL2promotion, CUtensorMapFloatOOBfill);

__global__ void plain_kernel(const __nv_bfloat16* x, const __nv_bfloat16* w, const __nv_bfloat16* b, __nv_bfloat16* out, int ntok) {
    const int t0 = blockIdx.x * 8;
    for (int f = threadIdx.x; f < D; f += blockDim.x) {
        float acc[8] = {};
        for (int g = 0; g < D / 4; g++) {
            float v[4], m[4];
            for (int i = 0; i < 4; i++) { v[i] = __bfloat162float(w[(4 * g + i) * D + f]); m[i] = fabsf(v[i]); }
            const float thr = fmaxf(fminf(fmaxf(m[0], m[1]), fmaxf(m[2], m[3])), fmaxf(fminf(m[0], m[1]), fminf(m[2], m[3])));
            for (int i = 0; i < 4; i++)
                for (int t = 0; t < 8; t++)
                    if (m[i] >= thr && t0 + t < ntok) acc[t] += v[i] * __bfloat162float(x[(size_t)(t0 + t) * D + 4 * g + i]);
        }
        for (int t = 0; t < 8; t++)
            if (t0 + t < ntok) out[(size_t)(t0 + t) * D + f] = __hadd(__float2bfloat16(acc[t]), b[f]);
    }
}

extern "C" void kernel_launch(void* const* d_in, const int* in_sizes, int n_in, void* d_out, int out_size) {
    static EncodeFn enc = nullptr;
    static int ncl = 0, nhelp = 0;
    const int ntok = in_sizes[0] / D;
    cudaLaunchConfig_t cfg = {};
    cudaLaunchAttribute at[1];
    at[0].id = cudaLaunchAttributeClusterDimension; at[0].val.clusterDim.x = CL; at[0].val.clusterDim.y = 1; at[0].val.clusterDim.z = 1;
    cfg.blockDim = dim3(NTHREADS); cfg.dynamicSmemBytes = SMEM_BYTES; cfg.attrs = at; cfg.numAttrs = 1; cfg.stream = cudaStreamPerThread;
    if (!enc) {
        cudaDriverEntryPointQueryResult qr; void* fn = nullptr;
        cudaGetDriverEntryPoint("cuTensorMapEncodeTiled", &fn, cudaEnableDefault, &qr);
        enc = (EncodeFn)fn;
        cudaFuncSetAttribute(spgemm_kernel<false>, cudaFuncAttributeMaxDynamicSharedMemorySize, SMEM_BYTES);
        cudaFuncSetAttribute(spgemm_kernel<true>, cudaFuncAttributeMaxDynamicSharedMemorySize, SMEM_BYTES);
        int dev = 0, nsm = 0;
        cudaGetDevice(&dev);
        cudaDeviceGetAttribute(&nsm, cudaDevAttrMultiProcessorCount, dev);
        cfg.gridDim = dim3(CL * (nsm / CL));
        cudaOccupancyMaxActiveClusters(&ncl, spgemm_kernel<false>, &cfg);
        if (ncl < 1) ncl = 1;
        nhelp = nsm > CL * ncl ? (nsm - CL * ncl) / CL : 0;
        if (nhelp > 7) nhelp = 7;
    }
    if (ntok % 4096 || ntok < 16384 || ntok > 65536 || ncl < 2 || ncl > 64 || 8 * (ncl + nhelp) > ntok / 64) {
        plain_kernel<<<(ntok + 7) / 8, 192, 0, cudaStreamPerThread>>>((const __nv_bfloat16*)d_in[0], (const __nv_bfloat16*)d_in[1], (const __nv_bfloat16*)d_in[2], (__nv_bfloat16*)d_out, ntok);
        return;
    }
    Maps maps;
    for (int v = 0; v < 2; v++) {
        const cuuint32_t rows = v == 0 ? 2 : 1;
        const cuuint64_t pitch = (v == 0 ? 14 : 57) * D * 2;
        {
            cuuint64_t dims[4] = {64, (cuuint64_t)ntok, 8 / rows, 9};
            cuuint64_t strides[3] = {D * 2, pitch, 128};
            cuuint32_t box[4] = {64, rows, 8 / rows, 9}, es[4] = {1, 1, 1, 1};
            enc(&maps.x[v], CU_TENSOR_MAP_DATA_TYPE_BFLOAT16, 4, d_in[0], dims, strides, box, es, CU_TENSOR_MAP_INTERLEAVE_NONE,
                CU_TENSOR_MAP_SWIZZLE_128B, CU_TENSOR_MAP_L2_PROMOTION_L2_128B, CU_TENSOR_MAP_FLOAT_OOB_FILL_NONE);
        }
        {
            cuuint64_t dims[3] = {D, (cuuint64_t)ntok, 8 / rows};
            cuuint64_t strides[2] = {D * 2, pitch};
            cuuint32_t box[3] = {64, rows, 8 / rows}, es[3] = {1, 1, 1};
            enc(&maps.o[v], CU_TENSOR_MAP_DATA_TYPE_BFLOAT16, 3, d_out, dims, strides, box, es, CU_TENSOR_MAP_INTERLEAVE_NONE,
                CU_TENSOR_MAP_SWIZZLE_128B, CU_TENSOR_MAP_L2_PROMOTION_NONE, CU_TENSOR_MAP_FLOAT_OOB_FILL_NONE);
        }
    }
    {
        cuuint64_t dims[3] = {256, (cuuint64_t)ntok * D * 2 / 2048, 4};
        cuuint64_t strides[2] = {2048, 16384};
        cuuint32_t box[3] = {256, 4, 4}, es[3] = {1, 1, 1};
        enc(&maps.pf, CU_TENSOR_MAP_DATA_TYPE_FLOAT64, 3, d_in[0], dims, strides, box, es, CU_TENSOR_MAP_INTERLEAVE_NONE,
            CU_TENSOR_MAP_SWIZZLE_NONE, CU_TENSOR_MAP_L2_PROMOTION_NONE, CU_TENSOR_MAP_FLOAT_OOB_FILL_NONE);
    }
    Params p;
    p.w = (const uint16_t*)d_in[1]; p.bias = (const uint16_t*)d_in[2]; p.x = (const uint8_t*)d_in[0];
    p.nq = ntok / 64; p.npages = (int)(((size_t)ntok * D * 2) >> 21);
    const int nc = ncl, nh = nhelp;
    p.ncl = nc; p.nh = nh; p.nctas = CL * (nc + nh);
    p.m0 = (nc + nh) * XEARLY / 2;
    for (int h = 0; h < 8; h++) {
        const uint32_t R = p.nq - p.m0, H = h * (HT * p.nq / 1024 * 44 / (nc + nh));
        p.ratio[h] = h <= nh ? (H << 16) / (R - H) : 0;
        p.rm[h] = p.ratio[h] ? (((R - 1) << 16) + 0x7FFFu) / (0x10000u + p.ratio[h]) + 1 : R;
    }
    p.c0 = (p.m0 * 9) >> 3;
    p.tb = p.m0 + (NSLOT - XEARLY) * (nc + nh) / 2;
    p.ta = p.tb + 1 + (int)((p.nq - p.tb) * TAFRAC); p.te = (int)(p.nq * TEFRAC) + 2;
    p.slope0 = ((LEAD1 - LEAD0) << 16) / (p.ta - p.tb); p.slope1 = ((LEAD1 - LEADE) << 16) / (p.te - p.ta);
    cfg.gridDim = dim3(CL * nc);
    cudaLaunchKernelEx(&cfg, spgemm_kernel<false>, maps, p);
    if (nh) {
        at[0].id = cudaLaunchAttributeProgrammaticStreamSerialization; at[0].val.programmaticStreamSerializationAllowed = 1;
        cfg.gridDim = dim3(CL * nh);
        cudaLaunchKernelEx(&cfg, spgemm_kernel<true>, maps, p);
    }
}
```

```cpp
#include <cuda_runtime.h>
#include <cuda_bf16.h>
#include <cuda.h>
#include <stdint.h>

constexpr int D = 576;
constexpr int NT = 32;
constexpr int NSLOT = 5;
constexpr int XEARLY = 2;
constexpr int NSTAT = 4;
constexpr int DELTA = 24;
constexpr int HT = 44;
constexpr int LEAD0 = 140, LEAD1 = 310, LEADE = 40, PACE = 1200;
constexpr double TAFRAC = 0.249, TEFRAC = 0.97;
constexpr int NPR = 2, PWAIT = 1200;
constexpr int KSTEPS = 18;
constexpr int CL = 3;
constexpr int TILE_BYTES = NT * D * 2;
constexpr int STG_BYTES = NT * 128;
constexpr int NACC = NT / 2;
constexpr int NB = NT / 8;
constexpr int NCONS = 384;
constexpr int NTHREADS = 512;
constexpr int NTAB = 1024;
constexpr uint32_t NO_TILE = 0xFFFFFu;

constexpr int OFF_X = 0;
constexpr int OFF_WST = OFF_X + (NSLOT - 1) * TILE_BYTES;
constexpr int OFF_STG = OFF_X + NSLOT * TILE_BYTES;
constexpr int OFF_TAB = OFF_STG + 3 * STG_BYTES;
constexpr int OFF_TK = OFF_TAB + 16 * NTAB;
constexpr int OFF_MSK = OFF_TK + 128;
constexpr int OFF_INFO = OFF_MSK + 2 * 36 * 8;
constexpr int OFF_FULL = OFF_INFO + 32;
constexpr int OFF_EMPTY = OFF_FULL + 8 * NSLOT;
constexpr int OFF_MBAR = OFF_EMPTY + 8 * NSLOT;
constexpr int OFF_GO = OFF_MBAR + 16;
constexpr int OFF_PLAN = OFF_GO + 8;
constexpr int OFF_PLAN2 = OFF_PLAN + 8;
constexpr int SMEM_BYTES = OFF_PLAN2 + 8 + 1024;
static_assert(SMEM_BYTES <= 232448 && TILE_BYTES >= 192 * 128 && XEARLY % 2 == 0 && XEARLY < NSLOT && NSLOT < 8 && NB == 4 && OFF_INFO % 16 == 0, "layout");

__device__ __align__(128) uint4    g_afrag[9 * KSTEPS * 128];
__device__ __align__(128) uint4    g_aux[36 * 6 * 32];
__device__ __align__(128) uint2    g_rval[36 * 36 * 32];
__device__ __align__(128) uint32_t g_roff[36 * 36 * 32];
__device__ __align__(128) uint32_t g_ready[9 * 32];
__device__ __align__(128) uint32_t g_passed;
__device__ __align__(128) uint32_t g_ticket;
__device__ __align__(128) uint32_t g_done;
__device__ __align__(128) ulonglong2 g_plan;

__device__ __forceinline__ uint32_t max2(uint32_t a, uint32_t b) { uint32_t d; asm("max.u16x2 %0, %1, %2;" : "=r"(d) : "r"(a), "r"(b)); return d; }
__device__ __forceinline__ uint32_t min2(uint32_t a, uint32_t b) { uint32_t d; asm("min.u16x2 %0, %1, %2;" : "=r"(d) : "r"(a), "r"(b)); return d; }
__device__ __forceinline__ uint32_t sign2(uint32_t a) { uint32_t d; asm("prmt.b32 %0, %1, %1, 0xBB99;" : "=r"(d) : "r"(a)); return d; }
__device__ __forceinline__ void load_unit(uint32_t wsm, int ls, int unit, int lane, uint32_t (&m)[4]) {
    const int row = ls * 32 + (lane >> 4) * 16 + ((lane & 7) >> 1) * 4 + ((lane >> 3) & 1) * 2 + (lane & 1);
    const uint32_t ad = wsm + row * 128 + ((unit ^ ((row & 1) | ((row >> 1) & 6))) << 4);
    asm volatile("ldmatrix.sync.aligned.m8n8.x4.trans.shared.b16 {%0,%1,%2,%3}, [%4];" : "=r"(m[0]), "=r"(m[1]), "=r"(m[2]), "=r"(m[3]) : "r"(ad) : "memory");
}
__device__ __forceinline__ void zip4(uint32_t a01, uint32_t a23, uint32_t b01, uint32_t b23, uint32_t (&x)[4]) {
    x[0] = __byte_perm(a01, b01, 0x5410); x[1] = __byte_perm(a01, b01, 0x7632); x[2] = __byte_perm(a23, b23, 0x5410); x[3] = __byte_perm(a23, b23, 0x7632);
}
__device__ __forceinline__ void middle2(const uint32_t (&x)[4], uint32_t (&m)[4], uint32_t& u, uint32_t& v) {
#pragma unroll
    for (int i = 0; i < 4; i++) m[i] = x[i] & 0x7FFF7FFFu;
    u = min2(max2(m[0], m[1]), max2(m[2], m[3])); v = max2(min2(m[0], m[1]), min2(m[2], m[3]));
}
__device__ __forceinline__ int ties(uint32_t x0, uint32_t x1, uint32_t x2, uint32_t x3) {
    const uint32_t x[4] = {x0, x1, x2, x3};
    uint32_t m[4], u, v;
    middle2(x, m, u, v);
    const uint32_t t = u ^ v, f = u ^ min2(min2(m[0], m[1]), min2(m[2], m[3]));
    const bool t0 = (t & 0xFFFFu) == 0 && (v & 0xFFFFu) != 0, t1 = t < 0x10000u && v >= 0x10000u;
    return t0 + t1 + 2 * ((t0 && (f & 0xFFFFu) == 0) || (t1 && f < 0x10000u));
}
__device__ __forceinline__ void split(const uint32_t (&x)[4], bool dbl, bool P, uint32_t& alo, uint32_t& ahi, uint32_t& nib, uint32_t& va, uint32_t& vb) {
    uint32_t m[4], u, v;
    middle2(x, m, u, v);
    const uint32_t c = 0x80008000u - max2(max2(u, v), 0x00010001u);
    uint32_t k0 = sign2(m[0] + c), k1 = sign2(m[1] + c), k2 = sign2(m[2] + c), k3 = sign2(m[3] + c);
    const uint32_t three = (k0 & k1 & (k2 | k3)) | (k2 & k3 & (k0 | k1)), four = k0 & k1 & k2 & k3;
    const bool a2 = !dbl && P;
    const uint32_t pa = a2 ? k2 : k0, pb = dbl ? k2 : P ? k3 : k1;
    const uint32_t ra = three & pa, rb = three & pb & (four | ~pa);
    va = (a2 ? x[2] : x[0]) & ra; vb = (dbl ? x[2] : P ? x[3] : x[1]) & rb;
    if (a2) k2 &= ~ra; else k0 &= ~ra;
    if (dbl) k2 &= ~rb; else if (P) k3 &= ~rb; else k1 &= ~rb;
    const uint32_t s1 = k1 & k0, s2 = k2 & (k0 | k1);
    const uint32_t t = (k1 & x[1]) | (~k1 & k2 & x[2]);
    const uint32_t x0 = (k0 & x[0]) | (~k0 & t), x1 = (s1 & x[1]) | (s2 & x[2]) | (k3 & x[3]);
    nib = (~k0 & k1 & 0x00010001u) | (~k0 & ~k1 & 0x00020002u) | (~s2 & 0x00040004u) | (~s1 & 0x00080008u);
    alo = __byte_perm(x0, x1, 0x5410); ahi = __byte_perm(x0, x1, 0x7632);
}
__device__ __forceinline__ uint32_t resid_off(int g, int P, int r) {
    int k0 = 4 * g + 2 * P;
    int chunk = k0 >> 6, byte = (k0 & 63) * 2;
    return chunk * 1024 + r * 128 + (((byte >> 4) ^ r) << 4) + (byte & 15);
}
__device__ __forceinline__ void emit_step(const uint32_t (&lo)[4], const uint32_t (&hi)[4], uint32_t mm, uint32_t dd, int rb, int ks, int lane, uint32_t units, uint2 bias2) {
    uint32_t* const aux = (uint32_t*)(g_aux + rb * 6 * 32);
    auto put_slot = [&](int j, int ln, uint32_t v, uint32_t off) {
        uint16_t* o = j < 6 ? (uint16_t*)aux + (3 * 32 + ln) * 8 + j : (uint16_t*)g_roff + ((rb * 36 + (j >> 1)) * 32 + ln) * 2 + (j & 1);
        uint16_t* w = j < 6 ? (uint16_t*)aux + ((4 + (j >> 2)) * 32 + ln) * 8 + (j & 2) * 2 + (j & 1) : (uint16_t*)g_rval + ((rb * 36 + (j >> 1)) * 32 + ln) * 4 + (j & 1);
        o[0] = (uint16_t)off; w[0] = (uint16_t)v; w[2] = (uint16_t)(v >> 16);
    };
    const int r = lane >> 2, q = lane & 3, g0 = ks * 8 + q;
    const uint32_t gm = __shfl_sync(~0u, mm | (dd << 8), ks);
    const uint32_t md = mm | (dd << 8), c2 = __popc(md & 0x5555u) | (__popc(md & 0xAAAAu) << 16);
    const uint32_t tot = __reduce_add_sync(~0u, c2), pre = __reduce_add_sync(~0u, lane < ks ? c2 : 0u);
    const int ne = tot & 0xFFFF, no = tot >> 16;
    const uint32_t par = (q & 1) ? 0xAAAAu : 0x5555u;
    const int base = (q & 1) ? pre >> 16 : pre & 0xFFFF;
    const int rk0 = base + __popc(gm & par & (((1u << q) - 1) * 0x101u)), rk1 = base + __popc(gm & par & (((16u << q) - 1) * 0x101u));
    const bool d0 = (gm >> (8 + q)) & 1, d1 = (gm >> (12 + q)) & 1;
    uint32_t a[4], rs[4], x[4], w0, w1;
    zip4(lo[0], lo[1], hi[0], hi[1], x); split(x, d0, rk0 & 1, a[0], a[1], w0, rs[0], rs[1]);
    zip4(lo[2], lo[3], hi[2], hi[3], x); split(x, d1, rk1 & 1, a[2], a[3], w1, rs[2], rs[3]);
    const int mt = rb >> 2, tid = (rb & 3) * 32 + lane;
    g_afrag[(mt * KSTEPS + ks) * 128 + tid] = make_uint4(a[0], a[1], a[2], a[3]);
    w0 <<= 4 * q; w1 <<= 4 * q;
    w0 |= __shfl_xor_sync(~0u, w0, 1); w1 |= __shfl_xor_sync(~0u, w1, 1);
    w0 |= __shfl_xor_sync(~0u, w0, 2); w1 |= __shfl_xor_sync(~0u, w1, 2);
    if ((q >> 1) == (ks & 1)) aux[((ks >> 3) * 32 + lane) * 4 + ((ks >> 1) & 3)] = (q & 1) ? w1 : w0;
    const int em = min(ne, max(8, 16 - no)), om = min(no, 16 - em);
    const int odd = q & 1, m = odd ? om : em;
    auto place = [&](int rk) {
        const int t = 15 - rk;
        return rk >= m ? 16 + (odd ? ne - em : 0) + rk - m : rk < 8 ? (rk >> 1) * 4 + 2 * odd + (rk & 1) : (t >> 1) * 4 + 2 * (odd ^ 1) + (t & 1);
    };
#pragma unroll
    for (int e = 0; e < 2; e++) {
        const int rk = e ? rk1 : rk0;
        const bool dbl = e ? d1 : d0;
        const uint32_t va = rs[2 * e], vb = rs[2 * e + 1];
        const uint32_t second = (__ballot_sync(~0u, vb != 0) & (0x11111111u << q)) != 0 && !dbl;
        if ((gm >> (4 * e + q)) & 1) {
            const int sl = place(rk);
            put_slot(sl >> 2, r * 4 + (sl & 3), !dbl ? va | vb : (rk & 1) ? vb : va, resid_off(g0 + 4 * e, rk & 1, r) | (second << 15));
            if (dbl) { const int s2 = place(rk + 1); put_slot(s2 >> 2, r * 4 + (s2 & 3), (rk & 1) ? va : vb, resid_off(g0 + 4 * e, ~rk & 1, r)); }
        }
    }
    const int ntot = ne + no;
    const int ng = ntot > 16 ? (ntot + 3) >> 2 : min(4, (max(ne, no) + 1) >> 1);
    if (ks == 7) { aux[(2 * 32 + lane) * 4 + 1] = ng | (units << 8); *(uint2*)(aux + (2 * 32 + lane) * 4 + 2) = bias2;
        aux[(3 * 32 + lane) * 4 + 3] = 0; *(uint2*)(aux + (5 * 32 + lane) * 4 + 2) = make_uint2(0, 0);
    }
    const int idx = 2 * ks + (q & 1);
    const int frow = ks < 6 ? ks : ks == 6 ? ng - 1 : ng;
    const bool fill = ks < 4 ? !(idx < ((q >> 1) ? om : em) || (15 - idx) < ((q >> 1) ? em : om))
                             : (ks < 6 || (ng > 6 && (ks == 6 || (ks == 8 && (ng & 1))))) && 4 * frow + q >= ntot;
    if (fill) put_slot(frow, lane, 0, resid_off(q >> 1, q & 1, r));
}

template<int SEL> __device__ __forceinline__ void wgmma_sp(float (&d)[NACC], const uint32_t (&a)[4], uint64_t bdesc, uint32_t meta) {
    asm volatile("{\n.reg .pred p;\nsetp.ne.b32 p, %22, 0;\n"
        "wgmma.mma_async.sp.sync.aligned.m64n32k32.f32.bf16.bf16 {%0, %1, %2, %3, %4, %5, %6, %7, %8, %9, %10, %11, %12, %13, %14, %15}, {%16, %17, %18, %19}, %20, %21, %23, p, 1, 1, 0;\n}\n"
        : "+f"(d[0]), "+f"(d[1]), "+f"(d[2]), "+f"(d[3]), "+f"(d[4]), "+f"(d[5]), "+f"(d[6]), "+f"(d[7]), "+f"(d[8]), "+f"(d[9]), "+f"(d[10]), "+f"(d[11]), "+f"(d[12]), "+f"(d[13]), "+f"(d[14]), "+f"(d[15])
        : "r"(a[0]), "r"(a[1]), "r"(a[2]), "r"(a[3]), "l"(bdesc), "r"(meta), "r"(1), "n"(SEL));
}

__device__ __forceinline__ void mbar_init(uint32_t bar, uint32_t cnt) { asm volatile("mbarrier.init.shared::cta.b64 [%0], %1;" :: "r"(bar), "r"(cnt) : "memory"); }
__device__ __forceinline__ void mbar_expect_tx(uint32_t bar, uint32_t bytes) {
    asm volatile("mbarrier.arrive.expect_tx.shared::cta.b64 _, [%0], %1;" :: "r"(bar), "r"(bytes) : "memory");
}
__device__ __forceinline__ void mbar_arrive(uint32_t bar) { asm volatile("mbarrier.arrive.shared::cta.b64 _, [%0];" :: "r"(bar) : "memory"); }
__device__ __forceinline__ void mbar_arrive_cluster(uint32_t bar) { asm volatile("mbarrier.arrive.shared::cluster.b64 _, [%0];" :: "r"(bar) : "memory"); }
__device__ __forceinline__ bool mbar_try(uint32_t bar, uint32_t parity) {
    uint32_t ok;
    asm volatile("{\n.reg .pred p;\nmbarrier.try_wait.parity.shared::cta.b64 p, [%1], %2;\nselp.u32 %0, 1, 0, p;\n}\n" : "=r"(ok) : "r"(bar), "r"(parity) : "memory");
    return ok;
}
__device__ __forceinline__ bool mbar_test(uint32_t bar, uint32_t parity) {
    uint32_t ok;
    asm volatile("{\n.reg .pred p;\nmbarrier.test_wait.parity.shared::cta.b64 p, [%1], %2;\nselp.u32 %0, 1, 0, p;\n}\n" : "=r"(ok) : "r"(bar), "r"(parity) : "memory");
    return ok;
}
__device__ __forceinline__ void fail_if(bool c) { asm volatile("{\n.reg .pred p;\nsetp.ne.u32 p, %0, 0;\n@p st.volatile.global.u32 [%1], %0;\n}\n" :: "r"((uint32_t)c), "l"(0ull) : "memory"); }
__device__ __forceinline__ void mbar_wait(uint32_t bar, uint32_t parity) {
    int n = 0;
    while (!mbar_try(bar, parity)) fail_if(++n > (1 << 20));
}
__device__ __forceinline__ void st_async(uint32_t addr, uint32_t v, uint32_t bar) {
    asm volatile("st.async.weak.shared::cluster.mbarrier::complete_tx::bytes.u32 [%0], %1, [%2];" :: "r"(addr), "r"(v), "r"(bar) : "memory");
}
__device__ __forceinline__ uint32_t mapa(uint32_t a, uint32_t cta) { uint32_t d; asm("mapa.shared::cluster.u32 %0, %1, %2;" : "=r"(d) : "r"(a), "r"(cta)); return d; }
__device__ __forceinline__ uint32_t lds32(uint32_t a) { uint32_t v; asm volatile("ld.shared.b32 %0, [%1];" : "=r"(v) : "r"(a)); return v; }
__device__ __forceinline__ uint32_t lds32v(uint32_t a) { uint32_t v; asm volatile("ld.volatile.shared.b32 %0, [%1];" : "=r"(v) : "r"(a) : "memory"); return v; }
__device__ __forceinline__ void sts32(uint32_t a, uint32_t v) { asm volatile("st.shared.b32 [%0], %1;" :: "r"(a), "r"(v) : "memory"); }
__device__ __forceinline__ uint4 ldw(const uint4* a) { uint4 v; asm volatile("ld.weak.global.L1::no_allocate.v4.u32 {%0,%1,%2,%3}, [%4];" : "=r"(v.x), "=r"(v.y), "=r"(v.z), "=r"(v.w) : "l"(a) : "memory"); return v; }
__device__ __forceinline__ void mma_k8(float* c, uint2 a, uint32_t b) {
    asm volatile("mma.sync.aligned.m16n8k8.row.col.f32.bf16.bf16.f32 {%0,%1,%2,%3}, {%4,%5}, {%6}, {%0,%1,%2,%3};"
                 : "+f"(c[0]), "+f"(c[1]), "+f"(c[2]), "+f"(c[3]) : "r"(a.x), "r"(a.y), "r"(b));
}
__device__ __forceinline__ void mma_k16(float* d, uint2 a, uint2 a2, uint32_t b0, uint32_t b1, float c0, float c1, float c2, float c3) {
    asm volatile("mma.sync.aligned.m16n8k16.row.col.f32.bf16.bf16.f32 {%0,%1,%2,%3}, {%4,%5,%6,%7}, {%8,%9}, {%10,%11,%12,%13};"
                 : "=f"(d[0]), "=f"(d[1]), "=f"(d[2]), "=f"(d[3]) : "r"(a.x), "r"(a.y), "r"(a2.x), "r"(a2.y), "r"(b0), "r"(b1), "f"(c0), "f"(c1), "f"(c2), "f"(c3));
}
__device__ __forceinline__ uint32_t pack_bias(float lo, float hi, uint32_t bias2) {
    uint32_t p, o;
    asm("cvt.rn.bf16x2.f32 %0, %1, %2;" : "=r"(p) : "f"(hi), "f"(lo));
    asm("add.rn.bf16x2 %0, %1, %2;" : "=r"(o) : "r"(p), "r"(bias2));
    return o;
}

struct Params {
    const uint16_t* w; const uint16_t* bias; const uint8_t* x;
    int nq, npages;
    int ncl, nh;
    int nctas;
    int tb, ta, te, slope0, slope1, c0;
    int m0;
    uint32_t ratio[8]; int rm[8];
};
struct Maps { CUtensorMap x[2], o[2], pf; };
__device__ __forceinline__ uint4 entry_w(int M, int w, int q, int extra) {
    const int r = M - (M >> 6), o = (r * 9363) >> 16, t = r - 7 * o, odd = t & 1, n = t >> 1;
    const int u = w ^ o ^ odd;
    const int C = 8 * o + 2 * n + ((n ^ u) & 1), C2 = 8 * o + 6 + ((1 ^ u) & 1);
    const uint32_t ra = 57 * C - ((C * 7282) >> 16) + 4 * odd, rb = odd ? 57 * C2 - ((C2 * 7282) >> 16) + 4 + 2 * n : ra + 12;
    const uint32_t rm = 2048 * (2 * (M >> 6) + w) + 56;
    const bool mixed = (M & 63) == 63;
    return make_uint4(M | (mixed << 14) | (q << 17) | (extra << 18), mixed ? rm * 0x10001u + (512u << 16) : ra * 0x10001u + (2u << 16),
                      mixed ? rm * 0x10001u + (1024u | 1536u << 16) : (ra + (odd ? 4 : 10)) | (rb << 16), 0);
}
__device__ __forceinline__ uint4 entry(int M, int q, int extra, unsigned long long plan) {
    const int r = M - (M >> 6), page = (r * 2341) >> 16;
    return entry_w(M, (M & 63) == 63 ? q : q ^ (int)((plan >> page) & 1), q, extra);
}
__device__ __forceinline__ int frontier(const Params& p, int t) {
    t = max(t, p.tb);
    const int l = t < p.ta ? LEAD0 + ((p.slope0 * (t - p.tb)) >> 16) : LEADE + max(0, (p.slope1 * (p.te - t)) >> 16);
    return (min(p.nq, t + l) * 9) >> 3;
}
__device__ __forceinline__ uint4 cl_entry(const Params& p, int m, int q, uint32_t ratio, unsigned long long plan) {
    const int nb = (m * ratio + 0x8000u) >> 16, nb1 = m ? ((m - 1) * ratio + 0x8000u) >> 16 : 0;
    uint4 e = entry(p.m0 + m + nb, q, nb - nb1, plan);
    const int c0 = frontier(p, p.m0 + m - 1 + nb1);
    e.w = c0 | (frontier(p, p.m0 + m + nb) - c0) << 16;
    return e;
}
__device__ __forceinline__ int helpers(const Params& p, unsigned long long plan, int q) {
    const int h0 = min(max(((p.ncl + p.nh) >> 1) - (p.ncl - (int)((plan >> 48) & 0xFF)), 0), p.nh);
    return q ? p.nh - h0 : h0;
}
__device__ __forceinline__ void draw(uint32_t& v, uint32_t* ctr, uint32_t inc) {
    asm volatile("{\n.reg .pred p;\nelect.sync _|p, 0xffffffff;\n@p atom.relaxed.gpu.global.add.u32 %0, [%1], %2;\n}" : "+r"(v) : "l"(ctr), "r"(inc) : "memory");
}
__device__ __forceinline__ uint4 lds128v(uint32_t a) { uint4 v; asm volatile("ld.volatile.shared.v4.b32 {%0,%1,%2,%3}, [%4];" : "=r"(v.x), "=r"(v.y), "=r"(v.z), "=r"(v.w) : "r"(a) : "memory"); return v; }
__device__ __forceinline__ void sts128(uint32_t a, uint4 e) { asm volatile("st.shared.v4.b32 [%0], {%1,%2,%3,%4};" :: "r"(a), "r"(e.x), "r"(e.y), "r"(e.z), "r"(e.w) : "memory"); }

__device__ __forceinline__ const uint8_t* probe_line(const Params& p, int page, int cell, int line, int parity) {
    return p.x + ((size_t)page << 21) + cell * 65536 + ((__popc(cell & 0xB) ^ parity) & 1) * 4096 + line * 128;
}
__device__ __forceinline__ int near_parity(const Params& p, int page, int cell, int line, uint32_t scratch, uint32_t since) {
    int sum = 0;
#pragma unroll 1
    for (int e = -1; e < NPR; e++) {
        uint32_t a = 0, b = 0, t0, t1;
        asm volatile("{\n.reg .pred p;\nsetp.ge.s32 p, %4, 0;\n@p ld.global.cg.u32 %0, [%2];\n@p ld.global.cg.u32 %1, [%3];\n}"
                     : "+r"(a), "+r"(b) : "l"(probe_line(p, page, cell, line + e, e & 1)), "l"(probe_line(p, page, cell, line + e, ~e & 1)), "r"(e) : "memory");
        asm volatile("st.volatile.shared.u32 [%0], %1;" :: "r"(scratch), "r"(a) : "memory");
        asm volatile("mov.u32 %0, %%clock;" : "=r"(t0) :: "memory");
        asm volatile("st.volatile.shared.u32 [%0], %1;" :: "r"(scratch), "r"(b) : "memory");
        asm volatile("mov.u32 %0, %%clock;" : "=r"(t1) :: "memory");
        const int d = min(t1 - t0, 200u);
        sum = e < 0 ? 0 : (e & 1) ? sum + d : sum - d;
        while (t1 - since < PWAIT) asm volatile("mov.u32 %0, %%clock;" : "=r"(t1) :: "memory");
    }
    return sum > 0;
}

template <bool HELPER>
__global__ void __launch_bounds__(NTHREADS, 1)
spgemm_kernel(const __grid_constant__ Params p, const __grid_constant__ Maps maps) {
    extern __shared__ unsigned char smem_raw[];
    const uint32_t sb = ((uint32_t)__cvta_generic_to_shared(smem_raw) + 1023u) & ~1023u;
    const int tid = threadIdx.x, warp = __shfl_sync(~0u, tid >> 5, 0), lane = tid & 31;
    const int rank = blockIdx.x % CL, cid = blockIdx.x / CL;
    const uint32_t bar_full = sb + OFF_FULL, bar_empty = sb + OFF_EMPTY, tk = sb + OFF_TK;
    uint4 wv[4];
    const int wrow = warp * 16 + (lane & 3) * 4;
    uint32_t b0, b1;
    auto prep_load = [&](int mtile) {
        b0 = __ldg(p.bias + mtile * 64 + lane); b1 = __ldg(p.bias + mtile * 64 + 32 + lane);
#pragma unroll
        for (int j = 0; j < 4; j++) wv[j] = __ldg((const uint4*)(p.w + (rank * 192 + wrow + j) * D + mtile * 64 + (lane >> 2) * 8));
    };
    if (!HELPER && warp < 12) {
        asm volatile("barrier.cluster.arrive.relaxed.aligned;" ::: "memory");
        if (cid < 36) prep_load(cid >> 2);
    }

    if (warp >= 12) {
        asm volatile("setmaxnreg.dec.sync.aligned.u32 32;");
        const int ppage = warp == 15 ? p.npages - 1 : cid, pcell = warp == 15 ? cid & 31 : 30, pline = warp == 15 ? (cid >> 5) * NPR : 2 * NPR;
        const bool prober = !HELPER && rank == 0 && (warp == 15 || (warp == 14 && cid < p.npages));
        uint32_t tp;
        asm volatile("mov.u32 %0, %%clock;" : "=r"(tp) :: "memory");
        if (prober && lane < 2 * NPR) asm volatile("prefetch.global.L2 [%0];" :: "l"(probe_line(p, ppage, pcell, pline + (lane >> 1), lane & 1)) : "memory");
        if (tid == NCONS) {
#pragma unroll
            for (int s = 0; s < NSLOT; s++) { mbar_init(bar_full + 8 * s, 1); mbar_init(bar_empty + 8 * s, HELPER ? 3 : 3 * CL); }
#pragma unroll
            for (int j = 0; j < 8; j++) sts32(tk + 16 * j, 0);
            mbar_init(sb + OFF_MBAR, 1); mbar_init(sb + OFF_MBAR + 8, 1);
            mbar_init(sb + OFF_GO, HELPER ? 12 : 12 + CL); mbar_init(sb + OFF_PLAN, 1); mbar_init(sb + OFF_PLAN2, 1);
            asm volatile("fence.mbarrier_init.release.cluster;" ::: "memory");
            mbar_expect_tx(sb + OFF_MBAR, 36 * 8);
            if (!HELPER && rank != 0) mbar_expect_tx(sb + OFF_PLAN, 16);
        }
        if (tid == NCONS + 32) {
            asm volatile("prefetch.tensormap [%0];" :: "l"(&maps.x[0]) : "memory");
            if (!HELPER) asm volatile("griddepcontrol.launch_dependents;");
            asm volatile("prefetch.tensormap [%0];" :: "l"(&maps.pf) : "memory");
            asm volatile("prefetch.tensormap [%0];" :: "l"(&maps.x[1]) : "memory");
#pragma unroll
            for (int j = 0; j < 2; j++) asm volatile("prefetch.tensormap [%0];" :: "l"(&maps.o[j]) : "memory");
        }
        __syncwarp();
        auto wait_plan = [&]() -> uint4 {
            unsigned long long a, b; int n = 0;
            do { asm volatile("ld.relaxed.gpu.global.v2.u64 {%0, %1}, [%2];" : "=l"(a), "=l"(b) : "l"(&g_plan) : "memory"); fail_if(++n > (1 << 22)); }
            while (__any_sync(~0u, (int)(a >> 56) + (int)(b >> 56) != 2 * p.ncl));
            b &= (1ull << 56) - 1;
            const int side = (b >> cid) & 1, n1 = __popcll(b), below = __popcll(b & ((1ull << cid) - 1));
            a = ((a ^ b) & ((1ull << 40) - 1)) | (unsigned long long)n1 << 48;
            return make_uint4((uint32_t)a, (uint32_t)(a >> 32), side | (side ? below : cid - below) << 8 | (side ? n1 : p.ncl - n1) << 16, 0);
        };
        uint4 e0 = make_uint4(0, 0, 0, 0), e1 = e0;
        if (HELPER) {
            asm volatile("bar.sync 0;" ::: "memory");
            if (warp == 15) {
                const uint4 inf = wait_plan();
                const unsigned long long plan = inf.x | ((unsigned long long)inf.y << 32);
                int idx = cid, nh = helpers(p, plan, 0), q = 2 * nh < p.nh;
                if (q) nh = p.nh - nh;
                if (idx >= nh) { idx -= nh; nh = p.nh - nh; q ^= 1; }
                const uint32_t ratio = p.ratio[nh];
                const int rm = p.rm[nh], H = p.nq - p.m0 - rm;
                for (int j0 = 0; __any_sync(~0u, idx + (j0 - 1) * nh < H); j0 += 32) {
                    const int k = idx + (j0 + lane) * nh, mk = (((k + 1) << 16) - 0x8000u + ratio - 1) / ratio;
                    uint4 e = entry(p.m0 + min(mk, rm) + k, q, 0, plan);
                    if (k >= H) e.x = NO_TILE;
                    sts128(sb + OFF_TAB + 16 * (j0 + lane), e);
                }
                __syncwarp();
                if (lane == 0) mbar_arrive(sb + OFF_PLAN);
            }
        } else {
            asm volatile("barrier.cluster.arrive.relaxed.aligned;" ::: "memory");
            int side = 0;
            if (warp == 12) { e0 = entry_w(cid, 0, 0, 0); e1 = entry_w(cid, 1, 1, 0); }
            if (rank == 0 && warp >= 14) {
                if (prober) side = near_parity(p, ppage, pcell, pline, sb + OFF_INFO + 16 + 4 * (warp & 1), tp);
                if (lane == 0) asm volatile("red.relaxed.gpu.global.add.u64 [%0], %1;" :: "l"(warp == 14 ? &g_plan.x : &g_plan.y), "l"((1ull << 56) | (unsigned long long)side << cid) : "memory");
            }
            asm volatile("barrier.cluster.wait.aligned;" ::: "memory");
            if (warp >= 13) {
                if (warp == 15 && rank == 0) {
                    const uint4 inf = wait_plan();
                    if (lane == 0) sts128(sb + OFF_INFO, inf);
                    else if (lane < CL)
                        asm volatile("st.async.weak.shared::cluster.mbarrier::complete_tx::bytes.v4.u32 [%0], {%1, %2, %3, %4}, [%5];"
                                     :: "r"(mapa(sb + OFF_INFO, lane)), "r"(inf.x), "r"(inf.y), "r"(inf.z), "r"(inf.w), "r"(mapa(sb + OFF_PLAN, lane)) : "memory");
                }
                if (rank == 0) asm volatile("bar.sync 15, 96;" ::: "memory"); else mbar_wait(sb + OFF_PLAN, 0);
                const uint4 inf = lds128v(sb + OFF_INFO);
                const unsigned long long plan = inf.x | ((unsigned long long)inf.y << 32);
                const int nh = helpers(p, plan, inf.z & 1), rm = p.rm[nh], nc = inf.z >> 16;
                const uint32_t ratio = p.ratio[nh];
                if (warp == 15 && rank == 0) {
                    const int m = ((inf.z >> 8) & 0xFF) + min(lane, NSTAT - 1) * nc;
                    sts128(sb + OFF_TAB + 16 * m, cl_entry(p, m, inf.z & 1, ratio, plan));
                    __syncwarp();
                    if (lane == 0) { mbar_arrive(sb + OFF_PLAN); mbar_expect_tx(sb + OFF_PLAN2, 16 * (rm - NSTAT * nc)); }
                }
                const uint32_t rtab = mapa(sb + OFF_TAB, 0), rbar = mapa(sb + OFF_PLAN2, 0);
                for (int m0 = NSTAT * nc + 96 * (2 - rank); __any_sync(~0u, m0 < rm); m0 += 288) {
                    const int m = m0 + tid - (NCONS + 32);
                    const uint4 e = cl_entry(p, m, inf.z & 1, ratio, plan);
                    if (m < rm) asm volatile("st.async.weak.shared::cluster.mbarrier::complete_tx::bytes.v4.u32 [%0], {%1, %2, %3, %4}, [%5];"
                                             :: "r"(rtab + 16 * m), "r"(e.x), "r"(e.y), "r"(e.z), "r"(e.w), "r"(rbar) : "memory");
                }
            }
        }
        if (warp == 12) {
            if (!HELPER && rank != 0) {
                mbar_wait(sb + OFF_PLAN, 0);
                const uint4 inf = lds128v(sb + OFF_INFO);
                const unsigned long long plan = inf.x | ((unsigned long long)inf.y << 32);
                auto cell = [&](int c, int q) {
                    const int y = 32 * c - 2 + 4 * ((__popc(c & 0xB) ^ (int)(plan >> (c >> 5)) ^ q) & 1);
                    asm volatile("{\n.reg .pred p;\nelect.sync _|p, 0xffffffff;\n@p cp.async.bulk.prefetch.tensor.3d.L2.global.tile [%0, {%1, %2, %1}];\n}" :: "l"(&maps.pf), "r"(0), "r"(y) : "memory");
                };
                const int fe0 = frontier(p, 0), step = 2 * (inf.z >> 16);
                int u0 = p.c0 + 2 * ((inf.z >> 8) & 0xFF) + rank - 1;
                {
                    uint32_t t, due;
                    asm volatile("mov.u32 %0, %%clock;" : "=r"(due) :: "memory");
                    due += (PACE * (u0 - p.c0)) / step;
                    for (; __any_sync(~0u, u0 < fe0); u0 += step, due += PACE) {
                        do { asm volatile("mov.u32 %0, %%clock;" : "=r"(t) :: "memory"); } while (__any_sync(~0u, (int)(t - due) < 0));
                        cell(u0, inf.z & 1);
                    }
                }
                for (int j = XEARLY + rank - 1;; j += 2) {
                    uint4 v; uint32_t ahead;
                    for (int n = 0; __any_sync(~0u, (ahead = (((v = lds128v(tk + ((j & 7) << 4))).x >> 20) - (j + 1)) & 0xFFF) >= 0x800); n++) {
                        if (__any_sync(~0u, lds32v(tk + (((j - 1) & 7) << 4)) == (NO_TILE | (uint32_t)j << 20))) { v.x = NO_TILE; break; }
                        __nanosleep(100); fail_if(n > (1 << 24));
                    }
                    if (__any_sync(~0u, (v.x & NO_TILE) == NO_TILE)) break;
                    j += __reduce_max_sync(~0u, ahead);
                    for (int u = v.w & 0xFFFF; __any_sync(~0u, u < (v.w & 0xFFFF) + (v.w >> 16)); u++) cell(u, (v.x >> 17) & 1);
                }
            } else {
                const uint32_t rtk = HELPER ? tk : mapa(tk, lane < CL ? lane : 0), rfull = HELPER ? bar_full : mapa(bar_full, lane < CL ? lane : 0);
                int s = 0; uint32_t ph = 1;
                uint64_t pol;
                if (!HELPER) asm volatile("createpolicy.fractional.L2::evict_first.b64 %0, 1.0;" : "=l"(pol));
                else asm volatile("createpolicy.fractional.L2::evict_normal.b64 %0, 1.0;" : "=l"(pol));
                auto request = [&](int j, const uint4& t) {
                    const bool valid = t.x != NO_TILE;
                    const CUtensorMap* tm = &maps.x[(t.x >> 14) & 1];
                    mbar_wait(bar_empty + 8 * s, ph);
                    if (__any_sync(~0u, valid)) {
                        const uint32_t dst = sb + OFF_X + s * TILE_BYTES;
                        if (HELPER)
                            asm volatile("{\n.reg .pred p;\nelect.sync _|p, 0xffffffff;\n"
                                         "@p cp.async.bulk.tensor.4d.shared::cluster.global.mbarrier::complete_tx::bytes.L2::cache_hint [%0], [%4, {%6, %7, %6, %6}], [%5], %11;\n"
                                         "@p cp.async.bulk.tensor.4d.shared::cluster.global.mbarrier::complete_tx::bytes.L2::cache_hint [%1], [%4, {%6, %8, %6, %6}], [%5], %11;\n"
                                         "@p cp.async.bulk.tensor.4d.shared::cluster.global.mbarrier::complete_tx::bytes.L2::cache_hint [%2], [%4, {%6, %9, %6, %6}], [%5], %11;\n"
                                         "@p cp.async.bulk.tensor.4d.shared::cluster.global.mbarrier::complete_tx::bytes.L2::cache_hint [%3], [%4, {%6, %10, %6, %6}], [%5], %11;\n}\n"
                                         :: "r"(dst), "r"(dst + 9216), "r"(dst + 2 * 9216), "r"(dst + 3 * 9216), "l"(tm), "r"(bar_full + 8 * s), "r"(0),
                                            "r"(t.y & 0xFFFF), "r"(t.y >> 16), "r"(t.z & 0xFFFF), "r"(t.z >> 16), "l"(pol) : "memory");
                        else
                            asm volatile("{\n.reg .pred p;\nelect.sync _|p, 0xffffffff;\n"
                                         "@p cp.async.bulk.tensor.4d.shared::cluster.global.mbarrier::complete_tx::bytes.multicast::cluster.L2::cache_hint [%0], [%4, {%6, %7, %6, %6}], [%5], %11, %12;\n"
                                         "@p cp.async.bulk.tensor.4d.shared::cluster.global.mbarrier::complete_tx::bytes.multicast::cluster.L2::cache_hint [%1], [%4, {%6, %8, %6, %6}], [%5], %11, %12;\n"
                                         "@p cp.async.bulk.tensor.4d.shared::cluster.global.mbarrier::complete_tx::bytes.multicast::cluster.L2::cache_hint [%2], [%4, {%6, %9, %6, %6}], [%5], %11, %12;\n"
                                         "@p cp.async.bulk.tensor.4d.shared::cluster.global.mbarrier::complete_tx::bytes.multicast::cluster.L2::cache_hint [%3], [%4, {%6, %10, %6, %6}], [%5], %11, %12;\n}\n"
                                         :: "r"(dst), "r"(dst + 9216), "r"(dst + 2 * 9216), "r"(dst + 3 * 9216), "l"(tm), "r"(bar_full + 8 * s), "r"(0),
                                            "r"(t.y & 0xFFFF), "r"(t.y >> 16), "r"(t.z & 0xFFFF), "r"(t.z >> 16), "h"((uint16_t)((1u << CL) - 1)), "l"(pol) : "memory");
                    }
                    if (HELPER) {
                        if (lane == 0) { sts128(tk + ((j & 7) << 4), t); mbar_expect_tx(bar_full + 8 * s, valid ? TILE_BYTES : 0); }
                    } else if (lane < CL) {
                        asm volatile("mbarrier.arrive.expect_tx.shared::cluster.b64 _, [%0], %1;" :: "r"(rfull + 8 * s), "r"(valid ? TILE_BYTES + 16 : 16) : "memory");
                        asm volatile("st.async.weak.shared::cluster.mbarrier::complete_tx::bytes.v4.u32 [%0], {%1, %2, %3, %4}, [%5];"
                                     :: "r"(rtk + ((j & 7) << 4)), "r"(t.x | ((uint32_t)(j + 1) << 20)), "r"(t.y), "r"(t.z), "r"(t.w), "r"(rfull + 8 * s) : "memory");
                    }
                    if (++s == NSLOT) { s = 0; ph ^= 1; }
                };
                if (HELPER) {
#pragma unroll 1
                    for (int j = 0; j < XEARLY; j++) request(j, entry_w(p.ncl + cid + (j >> 1) * (p.ncl + p.nh), j & 1, j & 1, 0));
                    mbar_wait(sb + OFF_PLAN, 0);
                    mbar_wait(sb + OFF_GO, 0);
                    for (int j = XEARLY;; j++) {
                        const uint4 t = lds128v(sb + OFF_TAB + 16 * (j - XEARLY));
                        request(j, t);
                        if (__any_sync(~0u, t.x == NO_TILE)) break;
                    }
                } else {
                    static_assert(XEARLY == 2, "");
                    request(0, e0);
                    request(1, e1);
                    mbar_wait(sb + OFF_PLAN, 0);
                    const uint4 inf = lds128v(sb + OFF_INFO);
                    const unsigned long long plan = inf.x | ((unsigned long long)inf.y << 32);
                    const int side = inf.z & 1, nc = inf.z >> 16;
                    const int nh = helpers(p, plan, side), rm = p.rm[nh], rmo = p.rm[p.nh - nh];
                    const uint32_t ratio = p.ratio[nh], ratioo = p.ratio[p.nh - nh];
                    const int st = NSTAT * nc, sto = NSTAT * (p.ncl - nc);
                    uint4 t = lds128v(sb + OFF_TAB + 16 * ((inf.z >> 8) & 0xFF));
                    mbar_wait(sb + OFF_GO, 0);
                    int j = XEARLY;
#pragma unroll 1
                    for (; j < XEARLY + NSTAT - 2; j++) {
                        const uint4 tn = lds128v(sb + OFF_TAB + 16 * (((inf.z >> 8) & 0xFF) + (j + 1 - XEARLY) * nc));
                        request(j, t);
                        t = tn;
                    }
                    uint32_t drawn = 0;
                    int q = side;
                    request(j++, t);
                    draw(drawn, &g_ticket, 1u << (16 * side));
                    t = lds128v(sb + OFF_TAB + 16 * (((inf.z >> 8) & 0xFF) + (NSTAT - 1) * nc));
                    mbar_wait(sb + OFF_PLAN2, 0);
                    for (;; j++) {
                        request(j, t);
                        uint32_t v = __reduce_max_sync(~0u, drawn);
                        int m = st + ((v >> (16 * side)) & 0xFFFF), mo = sto + ((v >> (16 - 16 * side)) & 0xFFFF);
                        if (q == side ? m >= rm && mo < rmo : mo >= rmo && m < rm) {
                            q ^= 1;
                            draw(drawn, &g_ticket, 1u << (16 * q));
                            v = __reduce_max_sync(~0u, drawn);
                            m = st + ((v >> (16 * side)) & 0xFFFF); mo = sto + ((v >> (16 - 16 * side)) & 0xFFFF);
                        }
                        if (q == side ? m >= rm : mo >= rmo) break;
                        const bool own = q == side;
                        q = m + ((m * ratio) >> 16) > mo + ((mo * ratioo) >> 16) + DELTA ? side ^ 1 : side;
                        draw(drawn, &g_ticket, 1u << (16 * q));
                        if (own) t = lds128v(sb + OFF_TAB + 16 * m);
                        else t = cl_entry(p, mo, side ^ 1, ratioo, plan);
                    }
                    t.x = NO_TILE;
                    request(j + 1, t);
                    if (lane == 0 && atomicInc(&g_done, p.ncl - 1) == (uint32_t)p.ncl - 1) g_ticket = 0;
                }
            }
        } else {
            const int g = warp - 13;
            uint64_t spol;
            asm volatile("createpolicy.fractional.L2::evict_first.b64 %0, 1.0;" : "=l"(spol));
            mbar_wait(sb + OFF_GO, 0);
            if (g == 2 && lane == 0 && atomicInc(&g_passed, p.nctas - 1) == (uint32_t)p.nctas - 1) {
#pragma unroll
                for (int m = 0; m < 9; m++) g_ready[m * 32] = 0;
                g_plan = make_ulonglong2(0, 0);
            }
            __syncwarp();
            for (int i = 0;; i++) {
                asm volatile("bar.arrive %0, 160;" :: "r"(12 + g) : "memory");
                asm volatile("bar.sync %0, 160;" :: "r"(1 + g) : "memory");
                const uint4 t = lds128v(tk + ((i & 7) << 4));
                if ((t.x & NO_TILE) == NO_TILE) break;
                const CUtensorMap* tm = &maps.o[(t.x >> 14) & 1];
                const int row[4] = {(int)(t.y & 0xFFFF), (int)(t.y >> 16), (int)(t.z & 0xFFFF), (int)(t.z >> 16)};
                if (lane == 0) {
#pragma unroll
                    for (int k = 0; k < 4; k++)
                        asm volatile("cp.async.bulk.tensor.3d.global.shared::cta.bulk_group.L2::cache_hint [%0, {%2, %3, %4}], [%1], %5;"
                                     :: "l"(tm), "r"(sb + OFF_STG + g * STG_BYTES + k * 1024), "r"((g * 3 + rank) * 64), "r"(row[k]), "r"(0), "l"(spol) : "memory");
                    asm volatile("cp.async.bulk.commit_group;" ::: "memory");
                    asm volatile("cp.async.bulk.wait_group.read 0;" ::: "memory");
                }
                __syncwarp();
            }
        }
        __syncwarp();
        if (!HELPER) asm volatile("barrier.cluster.arrive.relaxed.aligned;\nbarrier.cluster.wait.aligned;" ::: "memory");
    } else {
        asm volatile("setmaxnreg.inc.sync.aligned.u32 160;");
        const int wg = warp >> 2, wtid = tid & 127, r = lane >> 2;
        if (HELPER) asm volatile("bar.sync 0;" ::: "memory");
        else {
            int prb = cid;
            if (prb >= 36) asm volatile("barrier.cluster.wait.aligned;" ::: "memory");
#pragma unroll 1
            for (int round = 0; prb < 36; prb += p.ncl, round++) {
                const uint32_t wsm = sb + OFF_WST, msk = sb + OFF_MSK + (round & 1) * 288, mbar = sb + OFF_MBAR + (round & 1) * 8;
                if (round) {
                    asm volatile("bar.sync 3, 384;" ::: "memory");
                    if (tid == 0) mbar_expect_tx(mbar, 36 * 8);
                    prep_load(prb >> 2);
                }
                const int nt = ties(wv[0].x, wv[1].x, wv[2].x, wv[3].x) + ties(wv[0].y, wv[1].y, wv[2].y, wv[3].y) +
                               ties(wv[0].z, wv[1].z, wv[2].z, wv[3].z) + ties(wv[0].w, wv[1].w, wv[2].w, wv[3].w);
                const uint32_t mk = __ballot_sync(~0u, nt > 0), md = __ballot_sync(~0u, nt > 1);
                if (round == 0) asm volatile("barrier.cluster.wait.aligned;" ::: "memory");
                if (lane < CL)
                    asm volatile("st.async.weak.shared::cluster.mbarrier::complete_tx::bytes.v2.u32 [%0], {%1, %2}, [%3];"
                                 :: "r"(mapa(msk + (rank * 12 + warp) * 8, lane)), "r"(mk), "r"(md), "r"(mapa(mbar, lane)) : "memory");
#pragma unroll
                for (int j = 0; j < 4; j++) {
                    const int row = wrow + j;
                    const uint32_t ad = wsm + row * 128 + (((lane >> 2) ^ ((row & 1) | ((row >> 1) & 6))) << 4);
                    asm volatile("st.shared.v4.b32 [%0], {%1,%2,%3,%4};" :: "r"(ad), "r"(wv[j].x), "r"(wv[j].y), "r"(wv[j].z), "r"(wv[j].w) : "memory");
                }
                if (warp >= 6) asm volatile("bar.arrive 1, 384;" ::: "memory");
                else {
                    asm volatile("bar.sync 1, 384;" ::: "memory");
                    mbar_wait(mbar, (round >> 1) & 1);
                    uint4 ms = make_uint4(0, 0, 0, 0);
                    if (lane < KSTEPS) ms = lds128v(msk + 16 * lane);
                    const uint32_t m0 = ms.x, m1 = ms.z;
                    uint32_t c0 = m0 - ((m0 >> 1) & 0x55555555u), c1 = m1 - ((m1 >> 1) & 0x55555555u);
                    c0 = (c0 & 0x33333333u) + ((c0 >> 2) & 0x33333333u) + (c1 & 0x33333333u) + ((c1 >> 2) & 0x33333333u);
                    c1 = __reduce_add_sync(~0u, (c0 >> 4) & 0x0F0F0F0Fu); c0 = __reduce_add_sync(~0u, c0 & 0x0F0F0F0Fu);
                    auto key = [&](int v) { return ((((v & 1) ? c1 : c0) >> (4 * (v & 6))) & 0xFFu) * 8 + v; };
                    const uint32_t ku = key(lane & 7);
                    int rk = (key(2 * (lane >> 3)) < ku) + (key(2 * (lane >> 3) + 1) < ku);
                    rk += __shfl_xor_sync(~0u, rk, 8); rk += __shfl_xor_sync(~0u, rk, 16);
                    const int pp = prb & 3;
                    const int ulo = __ffs(__ballot_sync(~0u, rk == pp)) - 1, uhi = __ffs(__ballot_sync(~0u, rk == 7 - pp)) - 1;
                    uint32_t lo[4], hi[4];
                    load_unit(wsm, warp, ulo, lane, lo); load_unit(wsm, warp, uhi, lane, hi);
                    auto bits = [&](uint32_t a, uint32_t b, int u) { return ((a >> (4 * u)) & 15u) | (((b >> (4 * u)) & 15u) << 4); };
                    const uint32_t tl = bits(m0, m1, ulo), th = bits(m0, m1, uhi);
                    const uint2 bias2 = make_uint2(__shfl_sync(~0u, ulo < 4 ? b0 : b1, (ulo * 8 + r) & 31) * 0x10001u, __shfl_sync(~0u, uhi < 4 ? b0 : b1, (uhi * 8 + r) & 31) * 0x10001u);
                    emit_step(lo, hi, tl | th, (tl & th) | bits(ms.y, ms.w, ulo) | bits(ms.y, ms.w, uhi), prb, rank * 6 + warp, lane, ulo | (uhi << 4), bias2);
                    asm volatile("bar.sync 2, 192;" ::: "memory");
                    if (tid == 0) asm volatile("red.release.gpu.global.add.u32 [%0], 1;" :: "l"(&g_ready[(prb >> 2) * 32]) : "memory");
                }
            }
            if (warp == 0 && lane < CL) mbar_arrive_cluster(mapa(sb + OFF_GO, lane));
        }
        const int mt = wg * 3 + rank, rb = mt * 4 + (warp & 3);
        if ((warp & 3) == 0) {
            uint32_t v; int n = 0;
            do { asm volatile("ld.acquire.gpu.global.u32 %0, [%1];" : "=r"(v) : "l"(&g_ready[mt * 32]) : "memory"); fail_if(++n > (1 << 22)); } while (__any_sync(~0u, v < 4 * CL));
        }
        asm volatile("bar.sync %0, 128;" :: "r"(12 + wg) : "memory");
        if (wg > 0) asm volatile("bar.sync %0, 256;" :: "r"(7 + wg) : "memory");
        uint32_t a[KSTEPS][4], meta[9];
        uint2 rv[3]; uint32_t ro[3], sel[3];
        uint32_t info, bias_lo, bias_hi;
        {
            const uint4* ap = g_aux + rb * 6 * 32 + lane;
            const uint4 v3 = ldw(ap + 96), v2 = ldw(ap + 64), v4 = ldw(ap + 128), v5 = ldw(ap + 160), v0 = ldw(ap), v1 = ldw(ap + 32);
            meta[0] = v0.x; meta[1] = v0.y; meta[2] = v0.z; meta[3] = v0.w; meta[4] = v1.x; meta[5] = v1.y; meta[6] = v1.z; meta[7] = v1.w;
            meta[8] = v2.x; info = v2.y; bias_lo = v2.z; bias_hi = v2.w;
            ro[0] = v3.x; ro[1] = v3.y; ro[2] = v3.z;
            rv[0] = make_uint2(v4.x, v4.y); rv[1] = make_uint2(v4.z, v4.w); rv[2] = make_uint2(v5.x, v5.y);
        }
#pragma unroll
        for (int k = 0; k < KSTEPS; k++) { uint4 v = ldw(&g_afrag[(mt * KSTEPS + k) * 128 + wtid]); a[k][0] = v.x; a[k][1] = v.y; a[k][2] = v.z; a[k][3] = v.w; }
        if (wg < 2) asm volatile("bar.arrive %0, 256;" :: "r"(8 + wg) : "memory");
        if (lane == 0) mbar_arrive(sb + OFF_GO);
        auto selector = [](uint32_t o) { return 0x5410u + ((o >> 15) & 1) * 0x22u + (o >> 31) * 0x2200u; };
#pragma unroll
        for (int j = 0; j < 3; j++) { sel[j] = selector(ro[j]); ro[j] &= 0x7FFF7FFFu; }
        mbar_wait(bar_full, 0);
        info = __shfl_sync(~0u, info, 0);
        const int ngrp = info & 0xFF, ulo = (info >> 8) & 7, uhi = (info >> 12) & 7;
        const uint32_t stg = sb + OFF_STG + wg * STG_BYTES + ((lane >> 4) * 8 + (lane & 7)) * 128 + (((((lane >> 3) & 1) ? uhi : ulo) ^ (lane & 7)) << 4);
        const uint32_t rempty = HELPER ? bar_empty : mapa(bar_empty, 0);
        float acc[NACC];
        uint32_t bq[NB][6];
        auto gather = [&](uint32_t xb) {
#pragma unroll
            for (int j = 0; j < 4; j++) {
                const uint32_t o = xb + ((j & 1) ? ro[j >> 1] >> 16 : ro[j >> 1] & 0xFFFF);
#pragma unroll
                for (int n = 0; n < NB; n++) {
                    bq[n][j] = 0;
                    asm volatile("{\n.reg .pred p;\nsetp.lt.s32 p, %2, %3;\n@p ld.shared.b32 %0, [%1];\n}" : "+r"(bq[n][j]) : "r"(o + n * 9216), "r"(j), "r"(ngrp) : "memory");
                }
            }
#pragma unroll 1
            for (int z = 4; z < min(ngrp, 5); z++) {
#pragma unroll
                for (int n = 0; n < NB; n++) { bq[n][4] = lds32(xb + (ro[2] & 0xFFFF) + n * 9216); bq[n][5] = lds32(xb + (ro[2] >> 16) + n * 9216); }
            }
        };
        auto select = [&]() {
#pragma unroll
            for (int n = 0; n < NB; n++)
#pragma unroll
                for (int j = 0; j < 2; j++) bq[n][2 * j] = __byte_perm(bq[n][2 * j], bq[n][2 * j + 1], sel[j]);
        };
        auto further = [&](uint32_t xb, int bar) {
#pragma unroll 1
            for (int y = 4; y < min(ngrp, 5); y++) {
#pragma unroll
                for (int n = 0; n < NB; n++) mma_k8(acc + 4 * n, rv[2], __byte_perm(bq[n][4], bq[n][5], sel[2]));
                if (bar >= 0) asm volatile("bar.arrive %0, 256;" :: "r"(bar) : "memory");
#pragma unroll 1
                for (int z = 3; 2 * z < ngrp; z++) {
                    const uint2 v = __ldca(&g_rval[(rb * 36 + z) * 32 + lane]); const uint32_t off = __ldca(&g_roff[(rb * 36 + z) * 32 + lane]);
                    uint32_t bx[NB];
#pragma unroll
                    for (int n = 0; n < NB; n++) bx[n] = __byte_perm(lds32(xb + (off & 0x7FFF) + n * 9216), lds32(xb + ((off >> 16) & 0x7FFF) + n * 9216), selector(off));
#pragma unroll
                    for (int n = 0; n < NB; n++) mma_k8(acc + 4 * n, v, bx[n]);
                }
            }
        };
        bool more = true;
#pragma unroll
        for (int n = 0; n < NB; n++) bq[n][4] = bq[n][5] = 0;
        gather(sb + OFF_X);
        select();
#pragma unroll
        for (int n = 0; n < NB; n++) mma_k16(acc + 4 * n, rv[0], rv[1], bq[n][0], bq[n][2], 0.f, 0.f, 0.f, 0.f);
        further(sb + OFF_X, -1);
        const int bar_a = 8 + wg, bar_an = 8 + (wg + 2) % 3, bar_tn = 4 + (wg + 2) % 3;
        if (wg == 1) asm volatile("bar.arrive 4, 256;" ::: "memory");
        if (wg == 2) { asm volatile("bar.sync 10, 256;" ::: "memory"); asm volatile("bar.arrive 5, 256;" ::: "memory"); }
        int s = 0; uint32_t ph = 0;
        bool ready = false;
        for (int i = 0; more; i++) {
            const uint32_t xb = sb + OFF_X + s * TILE_BYTES;
            const int s1 = s + 1 == NSLOT ? 0 : s + 1;
            const uint32_t ph1 = s1 == 0 ? ph ^ 1 : ph;
            asm volatile("bar.sync %0, 256;" :: "r"(4 + wg) : "memory");
            const uint64_t desc = ((uint64_t)1 << 62) | ((uint64_t)(9216 >> 4) << 32) | ((uint64_t)1 << 16) | (uint64_t)(xb >> 4);
            asm volatile("wgmma.fence.sync.aligned;" ::: "memory");
#pragma unroll
            for (int k = 0; k < KSTEPS; k++) {
                const uint64_t d = desc + (uint64_t)(((k >> 1) * 1024 + (k & 1) * 64) >> 4);
                if (k & 1) wgmma_sp<1>(acc, a[k], d, meta[k >> 1]);
                else       wgmma_sp<0>(acc, a[k], d, meta[k >> 1]);
            }
            asm volatile("wgmma.commit_group.sync.aligned;" ::: "memory");
            asm volatile("bar.arrive %0, 256;" :: "r"(bar_an) : "memory");
            if (!ready) mbar_wait(bar_full + 8 * s1, ph1);
            const uint32_t tn = lds32v(tk + (((i + 1) & 7) << 4));
            gather(sb + OFF_X + s1 * TILE_BYTES);
            asm volatile("bar.sync %0, 160;" :: "r"(12 + wg) : "memory");
            asm volatile("wgmma.wait_group.sync.aligned 0;" ::: "memory");
            if (wtid == 0) { if (HELPER) mbar_arrive(bar_empty + 8 * s); else mbar_arrive_cluster(rempty + 8 * s); }
#pragma unroll
            for (int n = 0; n < NB; n += 2) {
                const uint32_t p0 = pack_bias(acc[4 * n], acc[4 * n + 1], bias_lo), p1 = pack_bias(acc[4 * n + 2], acc[4 * n + 3], bias_hi);
                const uint32_t p2 = pack_bias(acc[4 * n + 4], acc[4 * n + 5], bias_lo), p3 = pack_bias(acc[4 * n + 6], acc[4 * n + 7], bias_hi);
                if (n == 0) asm volatile("stmatrix.sync.aligned.m8n8.x4.trans.shared.b16 [%0], {%1,%2,%3,%4};" :: "r"(stg + n * 1024), "r"(p0), "r"(p1), "r"(p2), "r"(p3) : "memory");
                else asm volatile("{\n.reg .pred p;\nAGAIN:\nstmatrix.sync.aligned.m8n8.x4.trans.shared.b16 [%0], {%1,%2,%3,%4};\nsetp.eq.u32 p, %5, 0xFFFFFFFE;\n@p bra.uni AGAIN;\n}"
                                  :: "r"(stg + n * 1024), "r"(p0), "r"(p1), "r"(p2), "r"(p3), "r"(info) : "memory");
            }
            more = __any_sync(~0u, (tn & NO_TILE) != NO_TILE);
            select();
            if (wg != 2 || more) {
                asm volatile("{\n.reg .pred p;\nTURN:\nbar.sync %0, 256;\nsetp.eq.u32 p, %1, 0xFFFFFFFF;\n@p bra.uni TURN;\n}" :: "r"(bar_a), "r"(info) : "memory");
#pragma unroll
                for (int n = 0; n < NB; n++) {
                    mma_k16(acc + 4 * n, rv[0], rv[1], bq[n][0], bq[n][2], 0.f, 0.f, 0.f, 0.f);
                    if (n == 0) asm volatile("{\n.reg .pred p;\nsetp.le.s32 p, %1, 4;\n@p bar.arrive %0, 256;\n}" :: "r"(bar_tn), "r"(ngrp) : "memory");
                }
                further(sb + OFF_X + s1 * TILE_BYTES, bar_tn);
            }
            asm volatile("fence.proxy.async.shared::cta;" ::: "memory");
            asm volatile("bar.arrive %0, 160;" :: "r"(1 + wg) : "memory");
            s = s1; ph = ph1;
            ready = __all_sync(~0u, mbar_test(bar_full + 8 * (s + 1 == NSLOT ? 0 : s + 1), s + 1 == NSLOT ? ph ^ 1 : ph));
        }
        if (wg == 0) asm volatile("bar.sync 4, 256;" ::: "memory");
        asm volatile("bar.sync %0, 160;" :: "r"(12 + wg) : "memory");
        asm volatile("bar.arrive %0, 160;" :: "r"(1 + wg) : "memory");
        if (!HELPER) asm volatile("barrier.cluster.arrive.relaxed.aligned;\nbarrier.cluster.wait.aligned;" ::: "memory");
    }
}

typedef CUresult (*EncodeFn)(CUtensorMap*, CUtensorMapDataType, cuuint32_t, void*, const cuuint64_t*, const cuuint64_t*, const cuuint32_t*, const cuuint32_t*,
                             CUtensorMapInterleave, CUtensorMapSwizzle, CUtensorMapL2promotion, CUtensorMapFloatOOBfill);

__global__ void plain_kernel(const __nv_bfloat16* x, const __nv_bfloat16* w, const __nv_bfloat16* b, __nv_bfloat16* out, int ntok) {
    const int t0 = blockIdx.x * 8;
    for (int f = threadIdx.x; f < D; f += blockDim.x) {
        float acc[8] = {};
        for (int g = 0; g < D / 4; g++) {
            float v[4], m[4];
            for (int i = 0; i < 4; i++) { v[i] = __bfloat162float(w[(4 * g + i) * D + f]); m[i] = fabsf(v[i]); }
            const float thr = fmaxf(fminf(fmaxf(m[0], m[1]), fmaxf(m[2], m[3])), fmaxf(fminf(m[0], m[1]), fminf(m[2], m[3])));
            for (int i = 0; i < 4; i++)
                for (int t = 0; t < 8; t++)
                    if (m[i] >= thr && t0 + t < ntok) acc[t] += v[i] * __bfloat162float(x[(size_t)(t0 + t) * D + 4 * g + i]);
        }
        for (int t = 0; t < 8; t++)
            if (t0 + t < ntok) out[(size_t)(t0 + t) * D + f] = __hadd(__float2bfloat16(acc[t]), b[f]);
    }
}

extern "C" void kernel_launch(void* const* d_in, const int* in_sizes, int n_in, void* d_out, int out_size) {
    static EncodeFn enc = nullptr;
    static int ncl = 0, nhelp = 0;
    const int ntok = in_sizes[0] / D;
    cudaLaunchConfig_t cfg = {};
    cudaLaunchAttribute at[1];
    at[0].id = cudaLaunchAttributeClusterDimension; at[0].val.clusterDim.x = CL; at[0].val.clusterDim.y = 1; at[0].val.clusterDim.z = 1;
    cfg.blockDim = dim3(NTHREADS); cfg.dynamicSmemBytes = SMEM_BYTES; cfg.attrs = at; cfg.numAttrs = 1; cfg.stream = cudaStreamPerThread;
    if (!enc) {
        cudaDriverEntryPointQueryResult qr; void* fn = nullptr;
        cudaGetDriverEntryPoint("cuTensorMapEncodeTiled", &fn, cudaEnableDefault, &qr);
        enc = (EncodeFn)fn;
        cudaFuncSetAttribute(spgemm_kernel<false>, cudaFuncAttributeMaxDynamicSharedMemorySize, SMEM_BYTES);
        cudaFuncSetAttribute(spgemm_kernel<true>, cudaFuncAttributeMaxDynamicSharedMemorySize, SMEM_BYTES);
        int dev = 0, nsm = 0;
        cudaGetDevice(&dev);
        cudaDeviceGetAttribute(&nsm, cudaDevAttrMultiProcessorCount, dev);
        cfg.gridDim = dim3(CL * (nsm / CL));
        cudaOccupancyMaxActiveClusters(&ncl, spgemm_kernel<false>, &cfg);
        if (ncl < 1) ncl = 1;
        nhelp = nsm > CL * ncl ? (nsm - CL * ncl) / CL : 0;
        if (nhelp > 7) nhelp = 7;
    }
    if (ntok % 4096 || ntok < 16384 || ntok > 65536 || ncl < 2 || ncl > 56 || 8 * (ncl + nhelp) > ntok / 64) {
        plain_kernel<<<(ntok + 7) / 8, 192, 0, cudaStreamPerThread>>>((const __nv_bfloat16*)d_in[0], (const __nv_bfloat16*)d_in[1], (const __nv_bfloat16*)d_in[2], (__nv_bfloat16*)d_out, ntok);
        return;
    }
    Maps maps;
    for (int v = 0; v < 2; v++) {
        const cuuint32_t rows = v == 0 ? 2 : 1;
        const cuuint64_t pitch = (v == 0 ? 14 : 57) * D * 2;
        {
            cuuint64_t dims[4] = {64, (cuuint64_t)ntok, 8 / rows, 9};
            cuuint64_t strides[3] = {D * 2, pitch, 128};
            cuuint32_t box[4] = {64, rows, 8 / rows, 9}, es[4] = {1, 1, 1, 1};
            enc(&maps.x[v], CU_TENSOR_MAP_DATA_TYPE_BFLOAT16, 4, d_in[0], dims, strides, box, es, CU_TENSOR_MAP_INTERLEAVE_NONE,
                CU_TENSOR_MAP_SWIZZLE_128B, CU_TENSOR_MAP_L2_PROMOTION_L2_128B, CU_TENSOR_MAP_FLOAT_OOB_FILL_NONE);
        }
        {
            cuuint64_t dims[3] = {D, (cuuint64_t)ntok, 8 / rows};
            cuuint64_t strides[2] = {D * 2, pitch};
            cuuint32_t box[3] = {64, rows, 8 / rows}, es[3] = {1, 1, 1};
            enc(&maps.o[v], CU_TENSOR_MAP_DATA_TYPE_BFLOAT16, 3, d_out, dims, strides, box, es, CU_TENSOR_MAP_INTERLEAVE_NONE,
                CU_TENSOR_MAP_SWIZZLE_128B, CU_TENSOR_MAP_L2_PROMOTION_NONE, CU_TENSOR_MAP_FLOAT_OOB_FILL_NONE);
        }
    }
    {
        cuuint64_t dims[3] = {256, (cuuint64_t)ntok * D * 2 / 2048, 4};
        cuuint64_t strides[2] = {2048, 16384};
        cuuint32_t box[3] = {256, 4, 4}, es[3] = {1, 1, 1};
        enc(&maps.pf, CU_TENSOR_MAP_DATA_TYPE_FLOAT64, 3, d_in[0], dims, strides, box, es, CU_TENSOR_MAP_INTERLEAVE_NONE,
            CU_TENSOR_MAP_SWIZZLE_NONE, CU_TENSOR_MAP_L2_PROMOTION_NONE, CU_TENSOR_MAP_FLOAT_OOB_FILL_NONE);
    }
    Params p;
    p.w = (const uint16_t*)d_in[1]; p.bias = (const uint16_t*)d_in[2]; p.x = (const uint8_t*)d_in[0];
    p.nq = ntok / 64; p.npages = (int)(((size_t)ntok * D * 2) >> 21);
    const int nc = ncl, nh = nhelp;
    p.ncl = nc; p.nh = nh; p.nctas = CL * (nc + nh);
    p.m0 = (nc + nh) * XEARLY / 2;
    for (int h = 0; h < 8; h++) {
        const uint32_t R = p.nq - p.m0, H = h * (HT * p.nq / 1024 * 44 / (nc + nh));
        p.ratio[h] = h <= nh ? (H << 16) / (R - H) : 0;
        p.rm[h] = p.ratio[h] ? (((R - 1) << 16) + 0x7FFFu) / (0x10000u + p.ratio[h]) + 1 : R;
    }
    p.c0 = (p.m0 * 9) >> 3;
    p.tb = p.m0 + (NSLOT - XEARLY) * (nc + nh) / 2;
    p.ta = p.tb + 1 + (int)((p.nq - p.tb) * TAFRAC); p.te = (int)(p.nq * TEFRAC) + 2;
    p.slope0 = ((LEAD1 - LEAD0) << 16) / (p.ta - p.tb); p.slope1 = ((LEAD1 - LEADE) << 16) / (p.te - p.ta);
    cfg.gridDim = dim3(CL * nc);
    cudaLaunchKernelEx(&cfg, spgemm_kernel<false>, p, maps);
    if (nh) {
        at[0].id = cudaLaunchAttributeProgrammaticStreamSerialization; at[0].val.programmaticStreamSerializationAllowed = 1;
        cfg.gridDim = dim3(CL * nh);
        cudaLaunchKernelEx(&cfg, spgemm_kernel<true>, p, maps);
    }
}
```

```cpp
#include <cuda_runtime.h>
#include <cuda_bf16.h>
#include <cuda.h>
#include <stdint.h>

constexpr int D = 576;
constexpr int NT = 32;
constexpr int NSLOT = 5;
constexpr int XEARLY = 2;
constexpr int NSTAT = 4;
constexpr int DELTA = 24;
constexpr int HT = 44;
constexpr int LEAD0 = 140, LEAD1 = 310, LEADE = 40, PACE = 1200;
constexpr double TAFRAC = 0.249, TEFRAC = 0.97;
constexpr int NPR = 2, PWAIT = 1200;
constexpr int KSTEPS = 18;
constexpr int CL = 3;
constexpr int TILE_BYTES = NT * D * 2;
constexpr int STG_BYTES = NT * 128;
constexpr int NACC = NT / 2;
constexpr int NB = NT / 8;
constexpr int NCONS = 384;
constexpr int NTHREADS = 512;
constexpr int NTAB = 1024;
constexpr uint32_t NO_TILE = 0xFFFFFu;

constexpr int OFF_X = 0;
constexpr int OFF_WST = OFF_X + (NSLOT - 1) * TILE_BYTES;
constexpr int OFF_STG = OFF_X + NSLOT * TILE_BYTES;
constexpr int OFF_TAB = OFF_STG + 3 * STG_BYTES;
constexpr int OFF_TK = OFF_TAB + 16 * NTAB;
constexpr int OFF_MSK = OFF_TK + 128;
constexpr int OFF_INFO = OFF_MSK + 2 * 36 * 8;
constexpr int OFF_FULL = OFF_INFO + 32;
constexpr int OFF_EMPTY = OFF_FULL + 8 * NSLOT;
constexpr int OFF_MBAR = OFF_EMPTY + 8 * NSLOT;
constexpr int OFF_GO = OFF_MBAR + 16;
constexpr int OFF_PLAN = OFF_GO + 8;
constexpr int OFF_PLAN2 = OFF_PLAN + 8;
constexpr int SMEM_BYTES = OFF_PLAN2 + 8 + 1024;
static_assert(SMEM_BYTES <= 232448 && TILE_BYTES >= 192 * 128 && XEARLY % 2 == 0 && XEARLY < NSLOT && NSLOT < 8 && NB == 4 && OFF_INFO % 16 == 0, "layout");

__device__ __align__(128) uint4    g_afrag[9 * (KSTEPS + 1) * 128];
__device__ __align__(128) uint4    g_aux[36 * 6 * 32];
__device__ __align__(128) uint2    g_rval[36 * 36 * 32];
__device__ __align__(128) uint32_t g_roff[36 * 36 * 32];
__device__ __align__(128) uint32_t g_ready[9 * 32];
__device__ __align__(128) uint32_t g_passed;
__device__ __align__(128) uint32_t g_ticket;
__device__ __align__(128) uint32_t g_done;
__device__ __align__(128) ulonglong2 g_plan;

__device__ __forceinline__ uint32_t max2(uint32_t a, uint32_t b) { uint32_t d; asm("max.u16x2 %0, %1, %2;" : "=r"(d) : "r"(a), "r"(b)); return d; }
__device__ __forceinline__ uint32_t min2(uint32_t a, uint32_t b) { uint32_t d; asm("min.u16x2 %0, %1, %2;" : "=r"(d) : "r"(a), "r"(b)); return d; }
__device__ __forceinline__ uint32_t sign2(uint32_t a) { uint32_t d; asm("prmt.b32 %0, %1, %1, 0xBB99;" : "=r"(d) : "r"(a)); return d; }
__device__ __forceinline__ void load_unit(uint32_t wsm, int ls, int unit, int lane, uint32_t (&m)[4]) {
    const int row = ls * 32 + (lane >> 4) * 16 + ((lane & 7) >> 1) * 4 + ((lane >> 3) & 1) * 2 + (lane & 1);
    const uint32_t ad = wsm + row * 128 + ((unit ^ ((row & 1) | ((row >> 1) & 6))) << 4);
    asm volatile("ldmatrix.sync.aligned.m8n8.x4.trans.shared.b16 {%0,%1,%2,%3}, [%4];" : "=r"(m[0]), "=r"(m[1]), "=r"(m[2]), "=r"(m[3]) : "r"(ad) : "memory");
}
__device__ __forceinline__ void zip4(uint32_t a01, uint32_t a23, uint32_t b01, uint32_t b23, uint32_t (&x)[4]) {
    x[0] = __byte_perm(a01, b01, 0x5410); x[1] = __byte_perm(a01, b01, 0x7632); x[2] = __byte_perm(a23, b23, 0x5410); x[3] = __byte_perm(a23, b23, 0x7632);
}
__device__ __forceinline__ void middle2(const uint32_t (&x)[4], uint32_t (&m)[4], uint32_t& u, uint32_t& v) {
#pragma unroll
    for (int i = 0; i < 4; i++) m[i] = x[i] & 0x7FFF7FFFu;
    u = min2(max2(m[0], m[1]), max2(m[2], m[3])); v = max2(min2(m[0], m[1]), min2(m[2], m[3]));
}
__device__ __forceinline__ int ties(uint32_t x0, uint32_t x1, uint32_t x2, uint32_t x3) {
    const uint32_t x[4] = {x0, x1, x2, x3};
    uint32_t m[4], u, v;
    middle2(x, m, u, v);
    const uint32_t t = u ^ v, f = u ^ min2(min2(m[0], m[1]), min2(m[2], m[3]));
    const bool t0 = (t & 0xFFFFu) == 0 && (v & 0xFFFFu) != 0, t1 = t < 0x10000u && v >= 0x10000u;
    return t0 + t1 + 2 * ((t0 && (f & 0xFFFFu) == 0) || (t1 && f < 0x10000u));
}
__device__ __forceinline__ void split(const uint32_t (&x)[4], bool dbl, bool P, uint32_t& alo, uint32_t& ahi, uint32_t& nib, uint32_t& va, uint32_t& vb) {
    uint32_t m[4], u, v;
    middle2(x, m, u, v);
    const uint32_t c = 0x80008000u - max2(max2(u, v), 0x00010001u);
    uint32_t k0 = sign2(m[0] + c), k1 = sign2(m[1] + c), k2 = sign2(m[2] + c), k3 = sign2(m[3] + c);
    const uint32_t three = (k0 & k1 & (k2 | k3)) | (k2 & k3 & (k0 | k1)), four = k0 & k1 & k2 & k3;
    const bool a2 = !dbl && P;
    const uint32_t pa = a2 ? k2 : k0, pb = dbl ? k2 : P ? k3 : k1;
    const uint32_t ra = three & pa, rb = three & pb & (four | ~pa);
    va = (a2 ? x[2] : x[0]) & ra; vb = (dbl ? x[2] : P ? x[3] : x[1]) & rb;
    if (a2) k2 &= ~ra; else k0 &= ~ra;
    if (dbl) k2 &= ~rb; else if (P) k3 &= ~rb; else k1 &= ~rb;
    const uint32_t s1 = k1 & k0, s2 = k2 & (k0 | k1);
    const uint32_t t = (k1 & x[1]) | (~k1 & k2 & x[2]);
    const uint32_t x0 = (k0 & x[0]) | (~k0 & t), x1 = (s1 & x[1]) | (s2 & x[2]) | (k3 & x[3]);
    nib = (~k0 & k1 & 0x00010001u) | (~k0 & ~k1 & 0x00020002u) | (~s2 & 0x00040004u) | (~s1 & 0x00080008u);
    alo = __byte_perm(x0, x1, 0x5410); ahi = __byte_perm(x0, x1, 0x7632);
}
__device__ __forceinline__ uint32_t resid_off(int g, int P, int r) {
    int k0 = 4 * g + 2 * P;
    int chunk = k0 >> 6, byte = (k0 & 63) * 2;
    return chunk * 1024 + r * 128 + (((byte >> 4) ^ r) << 4) + (byte & 15);
}
__device__ __forceinline__ void emit_step(const uint32_t (&lo)[4], const uint32_t (&hi)[4], uint32_t md, int rb, int ks, int lane, uint32_t units, uint2 bias2, bool twice) {
    uint32_t* const aux = (uint32_t*)(g_aux + rb * 6 * 32);
    auto put_slot = [&](int j, int ln, uint32_t v, uint32_t off) {
        uint16_t* o = j < 6 ? (uint16_t*)aux + (3 * 32 + ln) * 8 + j : (uint16_t*)g_roff + ((rb * 36 + (j >> 1)) * 32 + ln) * 2 + (j & 1);
        uint16_t* w = j < 6 ? (uint16_t*)aux + ((4 + (j >> 2)) * 32 + ln) * 8 + (j & 2) * 2 + (j & 1) : (uint16_t*)g_rval + ((rb * 36 + (j >> 1)) * 32 + ln) * 4 + (j & 1);
        o[0] = (uint16_t)off; w[0] = (uint16_t)v; w[2] = (uint16_t)(v >> 16);
    };
    const int r = lane >> 2, q = lane & 3, g0 = ks * 8 + q;
    const uint32_t gm = __shfl_sync(~0u, md, ks);
    const uint32_t c2 = __popc(md & 0x5555u) | (__popc(md & 0xAAAAu) << 16);
    const uint32_t tot = __reduce_add_sync(~0u, c2), pre = __reduce_add_sync(~0u, lane < ks ? c2 : 0u);
    const int ne = tot & 0xFFFF, no = tot >> 16;
    const uint32_t par = (q & 1) ? 0xAAAAu : 0x5555u;
    const int base = (q & 1) ? pre >> 16 : pre & 0xFFFF;
    const int rk0 = base + __popc(gm & par & (((1u << q) - 1) * 0x101u)), rk1 = base + __popc(gm & par & (((16u << q) - 1) * 0x101u));
    const bool d0 = (gm >> (8 + q)) & 1, d1 = (gm >> (12 + q)) & 1;
    uint32_t a[4], rs[4], x[4], w0, w1;
    zip4(lo[0], lo[1], hi[0], hi[1], x); split(x, d0, rk0 & 1 && !twice, a[0], a[1], w0, rs[0], rs[1]);
    zip4(lo[2], lo[3], hi[2], hi[3], x); split(x, d1, rk1 & 1 && !twice, a[2], a[3], w1, rs[2], rs[3]);
    const int mt = rb >> 2, tid = (rb & 3) * 32 + lane;
    g_afrag[(mt * (KSTEPS + 1) + ks) * 128 + tid] = make_uint4(a[0], a[1], a[2], a[3]);
    if (twice) g_afrag[(mt * (KSTEPS + 1) + KSTEPS) * 128 + tid] =
        make_uint4(__byte_perm(rs[0], rs[1], 0x5410), __byte_perm(rs[0], rs[1], 0x7632), __byte_perm(rs[2], rs[3], 0x5410), __byte_perm(rs[2], rs[3], 0x7632));
    w0 <<= 4 * q; w1 <<= 4 * q;
    w0 |= __shfl_xor_sync(~0u, w0, 1); w1 |= __shfl_xor_sync(~0u, w1, 1);
    w0 |= __shfl_xor_sync(~0u, w0, 2); w1 |= __shfl_xor_sync(~0u, w1, 2);
    if ((q >> 1) == (ks & 1)) aux[((ks >> 3) * 32 + lane) * 4 + ((ks >> 1) & 3)] = (q & 1) ? w1 : w0;
    const int em = min(ne, max(8, 16 - no)), om = min(no, 16 - em);
    const int odd = q & 1, m = odd ? om : em;
    auto place = [&](int rk) {
        const int t = 15 - rk;
        return rk >= m ? 16 + (odd ? ne - em : 0) + rk - m : rk < 8 ? (rk >> 1) * 4 + 2 * odd + (rk & 1) : (t >> 1) * 4 + 2 * (odd ^ 1) + (t & 1);
    };
#pragma unroll
    for (int e = 0; e < 2; e++) {
        const int rk = e ? rk1 : rk0;
        const bool dbl = e ? d1 : d0;
        const uint32_t va = rs[2 * e], vb = rs[2 * e + 1];
        const uint32_t second = (__ballot_sync(~0u, vb != 0) & (0x11111111u << q)) != 0 && !dbl;
        if ((gm >> (4 * e + q)) & 1) {
            const int sl = place(rk);
            put_slot(sl >> 2, r * 4 + (sl & 3), !dbl ? va | vb : (rk & 1) ? vb : va, resid_off(g0 + 4 * e, rk & 1, r) | (second << 15));
            if (dbl) { const int s2 = place(rk + 1); put_slot(s2 >> 2, r * 4 + (s2 & 3), (rk & 1) ? va : vb, resid_off(g0 + 4 * e, ~rk & 1, r)); }
        }
    }
    const int ntot = ne + no;
    const int ng = ntot > 16 ? (ntot + 3) >> 2 : min(4, (max(ne, no) + 1) >> 1);
    if (ks == 7) { aux[(2 * 32 + lane) * 4 + 1] = ng | (units << 8); *(uint2*)(aux + (2 * 32 + lane) * 4 + 2) = bias2;
        aux[(3 * 32 + lane) * 4 + 3] = 0; *(uint2*)(aux + (5 * 32 + lane) * 4 + 2) = make_uint2(0, 0);
    }
    const int idx = 2 * ks + (q & 1);
    const int frow = ks < 6 ? ks : ks == 6 ? ng - 1 : ng;
    const bool fill = ks < 4 ? !(idx < ((q >> 1) ? om : em) || (15 - idx) < ((q >> 1) ? em : om))
                             : (ks < 6 || (ng > 6 && (ks == 6 || (ks == 8 && (ng & 1))))) && 4 * frow + q >= ntot;
    if (fill) put_slot(frow, lane, 0, resid_off(q >> 1, q & 1, r));
}

template<int SEL> __device__ __forceinline__ void wgmma_sp(float (&d)[NACC], const uint32_t (&a)[4], uint64_t bdesc, uint32_t meta) {
    asm volatile("{\n.reg .pred p;\nsetp.ne.b32 p, %22, 0;\n"
        "wgmma.mma_async.sp.sync.aligned.m64n32k32.f32.bf16.bf16 {%0, %1, %2, %3, %4, %5, %6, %7, %8, %9, %10, %11, %12, %13, %14, %15}, {%16, %17, %18, %19}, %20, %21, %23, p, 1, 1, 0;\n}\n"
        : "+f"(d[0]), "+f"(d[1]), "+f"(d[2]), "+f"(d[3]), "+f"(d[4]), "+f"(d[5]), "+f"(d[6]), "+f"(d[7]), "+f"(d[8]), "+f"(d[9]), "+f"(d[10]), "+f"(d[11]), "+f"(d[12]), "+f"(d[13]), "+f"(d[14]), "+f"(d[15])
        : "r"(a[0]), "r"(a[1]), "r"(a[2]), "r"(a[3]), "l"(bdesc), "r"(meta), "r"(1), "n"(SEL));
}

__device__ __forceinline__ void mbar_init(uint32_t bar, uint32_t cnt) { asm volatile("mbarrier.init.shared::cta.b64 [%0], %1;" :: "r"(bar), "r"(cnt) : "memory"); }
__device__ __forceinline__ void mbar_expect_tx(uint32_t bar, uint32_t bytes) {
    asm volatile("mbarrier.arrive.expect_tx.shared::cta.b64 _, [%0], %1;" :: "r"(bar), "r"(bytes) : "memory");
}
__device__ __forceinline__ void mbar_arrive(uint32_t bar) { asm volatile("mbarrier.arrive.shared::cta.b64 _, [%0];" :: "r"(bar) : "memory"); }
__device__ __forceinline__ void mbar_arrive_cluster(uint32_t bar) { asm volatile("mbarrier.arrive.shared::cluster.b64 _, [%0];" :: "r"(bar) : "memory"); }
__device__ __forceinline__ bool mbar_try(uint32_t bar, uint32_t parity) {
    uint32_t ok;
    asm volatile("{\n.reg .pred p;\nmbarrier.try_wait.parity.shared::cta.b64 p, [%1], %2;\nselp.u32 %0, 1, 0, p;\n}\n" : "=r"(ok) : "r"(bar), "r"(parity) : "memory");
    return ok;
}
__device__ __forceinline__ bool mbar_test(uint32_t bar, uint32_t parity) {
    uint32_t ok;
    asm volatile("{\n.reg .pred p;\nmbarrier.test_wait.parity.shared::cta.b64 p, [%1], %2;\nselp.u32 %0, 1, 0, p;\n}\n" : "=r"(ok) : "r"(bar), "r"(parity) : "memory");
    return ok;
}
__device__ __forceinline__ void fail_if(bool c) { asm volatile("{\n.reg .pred p;\nsetp.ne.u32 p, %0, 0;\n@p st.volatile.global.u32 [%1], %0;\n}\n" :: "r"((uint32_t)c), "l"(0ull) : "memory"); }
__device__ __forceinline__ void mbar_wait(uint32_t bar, uint32_t parity) {
    int n = 0;
    while (!mbar_try(bar, parity)) fail_if(++n > (1 << 20));
}
__device__ __forceinline__ void st_async(uint32_t addr, uint32_t v, uint32_t bar) {
    asm volatile("st.async.weak.shared::cluster.mbarrier::complete_tx::bytes.u32 [%0], %1, [%2];" :: "r"(addr), "r"(v), "r"(bar) : "memory");
}
__device__ __forceinline__ uint32_t mapa(uint32_t a, uint32_t cta) { uint32_t d; asm("mapa.shared::cluster.u32 %0, %1, %2;" : "=r"(d) : "r"(a), "r"(cta)); return d; }
__device__ __forceinline__ uint32_t lds32(uint32_t a) { uint32_t v; asm volatile("ld.shared.b32 %0, [%1];" : "=r"(v) : "r"(a)); return v; }
__device__ __forceinline__ uint32_t lds32v(uint32_t a) { uint32_t v; asm volatile("ld.volatile.shared.b32 %0, [%1];" : "=r"(v) : "r"(a) : "memory"); return v; }
__device__ __forceinline__ void sts32(uint32_t a, uint32_t v) { asm volatile("st.shared.b32 [%0], %1;" :: "r"(a), "r"(v) : "memory"); }
__device__ __forceinline__ uint4 ldw(const uint4* a) { uint4 v; asm volatile("ld.weak.global.L1::no_allocate.v4.u32 {%0,%1,%2,%3}, [%4];" : "=r"(v.x), "=r"(v.y), "=r"(v.z), "=r"(v.w) : "l"(a) : "memory"); return v; }
__device__ __forceinline__ void mma_k8(float* c, uint2 a, uint32_t b) {
    asm volatile("mma.sync.aligned.m16n8k8.row.col.f32.bf16.bf16.f32 {%0,%1,%2,%3}, {%4,%5}, {%6}, {%0,%1,%2,%3};"
                 : "+f"(c[0]), "+f"(c[1]), "+f"(c[2]), "+f"(c[3]) : "r"(a.x), "r"(a.y), "r"(b));
}
__device__ __forceinline__ void mma_k16(float* d, uint2 a, uint2 a2, uint32_t b0, uint32_t b1, float c0, float c1, float c2, float c3) {
    asm volatile("mma.sync.aligned.m16n8k16.row.col.f32.bf16.bf16.f32 {%0,%1,%2,%3}, {%4,%5,%6,%7}, {%8,%9}, {%10,%11,%12,%13};"
                 : "=f"(d[0]), "=f"(d[1]), "=f"(d[2]), "=f"(d[3]) : "r"(a.x), "r"(a.y), "r"(a2.x), "r"(a2.y), "r"(b0), "r"(b1), "f"(c0), "f"(c1), "f"(c2), "f"(c3));
}
__device__ __forceinline__ uint32_t pack_bias(float lo, float hi, uint32_t bias2) {
    uint32_t p, o;
    asm("cvt.rn.bf16x2.f32 %0, %1, %2;" : "=r"(p) : "f"(hi), "f"(lo));
    asm("add.rn.bf16x2 %0, %1, %2;" : "=r"(o) : "r"(p), "r"(bias2));
    return o;
}

struct Params {
    const uint16_t* w; const uint16_t* bias; const uint8_t* x;
    int nq, npages;
    int ncl, nh;
    int nctas;
    int tb, ta, te, slope0, slope1, c0;
    int m0;
    uint32_t ratio[8]; int rm[8];
};
struct Maps { CUtensorMap x[2], o[2], pf; };
__device__ __forceinline__ uint4 entry_w(int M, int w, int q, int extra) {
    const int r = M - (M >> 6), o = (r * 9363) >> 16, t = r - 7 * o, odd = t & 1, n = t >> 1;
    const int u = w ^ o ^ odd;
    const int C = 8 * o + 2 * n + ((n ^ u) & 1), C2 = 8 * o + 6 + ((1 ^ u) & 1);
    const uint32_t ra = 57 * C - ((C * 7282) >> 16) + 4 * odd, rb = odd ? 57 * C2 - ((C2 * 7282) >> 16) + 4 + 2 * n : ra + 12;
    const uint32_t rm = 2048 * (2 * (M >> 6) + w) + 56;
    const bool mixed = (M & 63) == 63;
    return make_uint4(M | (mixed << 14) | (q << 17) | (extra << 18), mixed ? rm * 0x10001u + (512u << 16) : ra * 0x10001u + (2u << 16),
                      mixed ? rm * 0x10001u + (1024u | 1536u << 16) : (ra + (odd ? 4 : 10)) | (rb << 16), 0);
}
__device__ __forceinline__ uint4 entry(int M, int q, int extra, unsigned long long plan) {
    const int r = M - (M >> 6), page = (r * 2341) >> 16;
    return entry_w(M, (M & 63) == 63 ? q : q ^ (int)((plan >> page) & 1), q, extra);
}
__device__ __forceinline__ int frontier(const Params& p, int t) {
    t = max(t, p.tb);
    const int l = t < p.ta ? LEAD0 + ((p.slope0 * (t - p.tb)) >> 16) : LEADE + max(0, (p.slope1 * (p.te - t)) >> 16);
    return (min(p.nq, t + l) * 9) >> 3;
}
__device__ __forceinline__ uint4 cl_entry(const Params& p, int m, int q, uint32_t ratio, unsigned long long plan) {
    const int nb = (m * ratio + 0x8000u) >> 16, nb1 = m ? ((m - 1) * ratio + 0x8000u) >> 16 : 0;
    uint4 e = entry(p.m0 + m + nb, q, nb - nb1, plan);
    const int c0 = frontier(p, p.m0 + m - 1 + nb1);
    e.w = c0 | (frontier(p, p.m0 + m + nb) - c0) << 16;
    return e;
}
__device__ __forceinline__ int helpers(const Params& p, unsigned long long plan, int q) {
    const int h0 = min(max(((p.ncl + p.nh) >> 1) - (p.ncl - (int)((plan >> 48) & 0xFF)), 0), p.nh);
    return q ? p.nh - h0 : h0;
}
__device__ __forceinline__ void draw(uint32_t& v, uint32_t* ctr, uint32_t inc) {
    asm volatile("{\n.reg .pred p;\nelect.sync _|p, 0xffffffff;\n@p atom.relaxed.gpu.global.add.u32 %0, [%1], %2;\n}" : "+r"(v) : "l"(ctr), "r"(inc) : "memory");
}
__device__ __forceinline__ uint4 lds128v(uint32_t a) { uint4 v; asm volatile("ld.volatile.shared.v4.b32 {%0,%1,%2,%3}, [%4];" : "=r"(v.x), "=r"(v.y), "=r"(v.z), "=r"(v.w) : "r"(a) : "memory"); return v; }
__device__ __forceinline__ void sts128(uint32_t a, uint4 e) { asm volatile("st.shared.v4.b32 [%0], {%1,%2,%3,%4};" :: "r"(a), "r"(e.x), "r"(e.y), "r"(e.z), "r"(e.w) : "memory"); }

__device__ __forceinline__ const uint8_t* probe_line(const Params& p, int page, int cell, int line, int parity) {
    return p.x + ((size_t)page << 21) + cell * 65536 + ((__popc(cell & 0xB) ^ parity) & 1) * 4096 + line * 128;
}
__device__ __forceinline__ int near_parity(const Params& p, int page, int cell, int line, uint32_t scratch, uint32_t since) {
    int sum = 0;
#pragma unroll 1
    for (int e = -1; e < NPR; e++) {
        uint32_t a = 0, b = 0, t0, t1;
        asm volatile("{\n.reg .pred p;\nsetp.ge.s32 p, %4, 0;\n@p ld.global.cg.u32 %0, [%2];\n@p ld.global.cg.u32 %1, [%3];\n}"
                     : "+r"(a), "+r"(b) : "l"(probe_line(p, page, cell, line + e, e & 1)), "l"(probe_line(p, page, cell, line + e, ~e & 1)), "r"(e) : "memory");
        asm volatile("st.volatile.shared.u32 [%0], %1;" :: "r"(scratch), "r"(a) : "memory");
        asm volatile("mov.u32 %0, %%clock;" : "=r"(t0) :: "memory");
        asm volatile("st.volatile.shared.u32 [%0], %1;" :: "r"(scratch), "r"(b) : "memory");
        asm volatile("mov.u32 %0, %%clock;" : "=r"(t1) :: "memory");
        const int d = min(t1 - t0, 200u);
        sum = e < 0 ? 0 : (e & 1) ? sum + d : sum - d;
        while (t1 - since < PWAIT) asm volatile("mov.u32 %0, %%clock;" : "=r"(t1) :: "memory");
    }
    return sum > 0;
}

template <bool HELPER>
__global__ void __launch_bounds__(NTHREADS, 1)
spgemm_kernel(const __grid_constant__ Params p, const __grid_constant__ Maps maps) {
    extern __shared__ unsigned char smem_raw[];
    const uint32_t sb = ((uint32_t)__cvta_generic_to_shared(smem_raw) + 1023u) & ~1023u;
    const int tid = threadIdx.x, warp = __shfl_sync(~0u, tid >> 5, 0), lane = tid & 31;
    const int rank = blockIdx.x % CL, cid = blockIdx.x / CL;
    const uint32_t bar_full = sb + OFF_FULL, bar_empty = sb + OFF_EMPTY, tk = sb + OFF_TK;
    uint4 wv[4];
    const int wrow = warp * 16 + (lane & 3) * 4;
    uint32_t b0, b1;
    auto prep_load = [&](int mtile) {
        b0 = __ldg(p.bias + mtile * 64 + lane); b1 = __ldg(p.bias + mtile * 64 + 32 + lane);
#pragma unroll
        for (int j = 0; j < 4; j++) wv[j] = __ldg((const uint4*)(p.w + (rank * 192 + wrow + j) * D + mtile * 64 + (lane >> 2) * 8));
    };
    if (!HELPER && warp < 12) {
        asm volatile("barrier.cluster.arrive.relaxed.aligned;" ::: "memory");
        if (cid < 36) prep_load(cid >> 2);
    }

    if (warp >= 12) {
        asm volatile("setmaxnreg.dec.sync.aligned.u32 32;");
        const int ppage = warp == 15 ? p.npages - 1 : cid, pcell = warp == 15 ? cid & 31 : 30, pline = warp == 15 ? (cid >> 5) * NPR : 2 * NPR;
        const bool prober = !HELPER && rank == 0 && (warp == 15 || (warp == 14 && cid < p.npages));
        uint32_t tp;
        asm volatile("mov.u32 %0, %%clock;" : "=r"(tp) :: "memory");
        if (prober && lane < 2 * NPR) asm volatile("prefetch.global.L2 [%0];" :: "l"(probe_line(p, ppage, pcell, pline + (lane >> 1), lane & 1)) : "memory");
        if (tid == NCONS) {
#pragma unroll
            for (int s = 0; s < NSLOT; s++) { mbar_init(bar_full + 8 * s, 1); mbar_init(bar_empty + 8 * s, HELPER ? 3 : 3 * CL); }
#pragma unroll
            for (int j = 0; j < 8; j++) sts32(tk + 16 * j, 0);
            mbar_init(sb + OFF_MBAR, 1); mbar_init(sb + OFF_MBAR + 8, 1);
            mbar_init(sb + OFF_GO, HELPER ? 12 : 12 + CL); mbar_init(sb + OFF_PLAN, 1); mbar_init(sb + OFF_PLAN2, 1);
            asm volatile("fence.mbarrier_init.release.cluster;" ::: "memory");
            mbar_expect_tx(sb + OFF_MBAR, 36 * 8);
            if (!HELPER && rank != 0) mbar_expect_tx(sb + OFF_PLAN, 16);
        }
        if (tid == NCONS + 32) {
            asm volatile("prefetch.tensormap [%0];" :: "l"(&maps.x[0]) : "memory");
            if (!HELPER) asm volatile("griddepcontrol.launch_dependents;");
            asm volatile("prefetch.tensormap [%0];" :: "l"(&maps.pf) : "memory");
            asm volatile("prefetch.tensormap [%0];" :: "l"(&maps.x[1]) : "memory");
#pragma unroll
            for (int j = 0; j < 2; j++) asm volatile("prefetch.tensormap [%0];" :: "l"(&maps.o[j]) : "memory");
        }
        __syncwarp();
        auto wait_plan = [&]() -> uint4 {
            unsigned long long a, b; int n = 0;
            do { asm volatile("ld.relaxed.gpu.global.v2.u64 {%0, %1}, [%2];" : "=l"(a), "=l"(b) : "l"(&g_plan) : "memory"); fail_if(++n > (1 << 22)); }
            while (__any_sync(~0u, (int)(a >> 56) + (int)(b >> 56) != 2 * p.ncl));
            b &= (1ull << 56) - 1;
            const int side = (b >> cid) & 1, n1 = __popcll(b), below = __popcll(b & ((1ull << cid) - 1));
            a = ((a ^ b) & ((1ull << 40) - 1)) | (unsigned long long)n1 << 48;
            return make_uint4((uint32_t)a, (uint32_t)(a >> 32), side | (side ? below : cid - below) << 8 | (side ? n1 : p.ncl - n1) << 16, 0);
        };
        uint4 e0 = make_uint4(0, 0, 0, 0), e1 = e0;
        if (HELPER) {
            asm volatile("bar.sync 0;" ::: "memory");
            if (warp == 15) {
                const uint4 inf = wait_plan();
                const unsigned long long plan = inf.x | ((unsigned long long)inf.y << 32);
                int idx = cid, nh = helpers(p, plan, 0), q = 2 * nh < p.nh;
                if (q) nh = p.nh - nh;
                if (idx >= nh) { idx -= nh; nh = p.nh - nh; q ^= 1; }
                const uint32_t ratio = p.ratio[nh];
                const int rm = p.rm[nh], H = p.nq - p.m0 - rm;
                for (int j0 = 0; __any_sync(~0u, idx + (j0 - 1) * nh < H); j0 += 32) {
                    const int k = idx + (j0 + lane) * nh, mk = (((k + 1) << 16) - 0x8000u + ratio - 1) / ratio;
                    uint4 e = entry(p.m0 + min(mk, rm) + k, q, 0, plan);
                    if (k >= H) e.x = NO_TILE;
                    sts128(sb + OFF_TAB + 16 * (j0 + lane), e);
                }
                __syncwarp();
                if (lane == 0) mbar_arrive(sb + OFF_PLAN);
            }
        } else {
            asm volatile("barrier.cluster.arrive.relaxed.aligned;" ::: "memory");
            int side = 0;
            if (warp == 12) { e0 = entry_w(cid, 0, 0, 0); e1 = entry_w(cid, 1, 1, 0); }
            if (rank == 0 && warp >= 14) {
                if (prober) side = near_parity(p, ppage, pcell, pline, sb + OFF_INFO + 16 + 4 * (warp & 1), tp);
                if (lane == 0) asm volatile("red.relaxed.gpu.global.add.u64 [%0], %1;" :: "l"(warp == 14 ? &g_plan.x : &g_plan.y), "l"((1ull << 56) | (unsigned long long)side << cid) : "memory");
            }
            asm volatile("barrier.cluster.wait.aligned;" ::: "memory");
            if (warp >= 13) {
                if (warp == 15 && rank == 0) {
                    const uint4 inf = wait_plan();
                    if (lane == 0) sts128(sb + OFF_INFO, inf);
                    else if (lane < CL)
                        asm volatile("st.async.weak.shared::cluster.mbarrier::complete_tx::bytes.v4.u32 [%0], {%1, %2, %3, %4}, [%5];"
                                     :: "r"(mapa(sb + OFF_INFO, lane)), "r"(inf.x), "r"(inf.y), "r"(inf.z), "r"(inf.w), "r"(mapa(sb + OFF_PLAN, lane)) : "memory");
                }
                if (rank == 0) asm volatile("bar.sync 15, 96;" ::: "memory"); else mbar_wait(sb + OFF_PLAN, 0);
                const uint4 inf = lds128v(sb + OFF_INFO);
                const unsigned long long plan = inf.x | ((unsigned long long)inf.y << 32);
                const int nh = helpers(p, plan, inf.z & 1), rm = p.rm[nh], nc = inf.z >> 16;
                const uint32_t ratio = p.ratio[nh];
                if (warp == 15 && rank == 0) {
                    const int m = ((inf.z >> 8) & 0xFF) + min(lane, NSTAT - 1) * nc;
                    sts128(sb + OFF_TAB + 16 * m, cl_entry(p, m, inf.z & 1, ratio, plan));
                    __syncwarp();
                    if (lane == 0) { mbar_arrive(sb + OFF_PLAN); mbar_expect_tx(sb + OFF_PLAN2, 16 * (rm - NSTAT * nc)); }
                }
                const uint32_t rtab = mapa(sb + OFF_TAB, 0), rbar = mapa(sb + OFF_PLAN2, 0);
                for (int m0 = NSTAT * nc + 96 * (2 - rank); __any_sync(~0u, m0 < rm); m0 += 288) {
                    const int m = m0 + tid - (NCONS + 32);
                    const uint4 e = cl_entry(p, m, inf.z & 1, ratio, plan);
                    if (m < rm) asm volatile("st.async.weak.shared::cluster.mbarrier::complete_tx::bytes.v4.u32 [%0], {%1, %2, %3, %4}, [%5];"
                                             :: "r"(rtab + 16 * m), "r"(e.x), "r"(e.y), "r"(e.z), "r"(e.w), "r"(rbar) : "memory");
                }
            }
        }
        if (warp == 12) {
            if (!HELPER && rank != 0) {
                mbar_wait(sb + OFF_PLAN, 0);
                const uint4 inf = lds128v(sb + OFF_INFO);
                const unsigned long long plan = inf.x | ((unsigned long long)inf.y << 32);
                auto cell = [&](int c, int q) {
                    const int y = 32 * c - 2 + 4 * ((__popc(c & 0xB) ^ (int)(plan >> (c >> 5)) ^ q) & 1);
                    asm volatile("{\n.reg .pred p;\nelect.sync _|p, 0xffffffff;\n@p cp.async.bulk.prefetch.tensor.3d.L2.global.tile [%0, {%1, %2, %1}];\n}" :: "l"(&maps.pf), "r"(0), "r"(y) : "memory");
                };
                const int fe0 = frontier(p, 0), step = 2 * (inf.z >> 16);
                int u0 = p.c0 + 2 * ((inf.z >> 8) & 0xFF) + rank - 1;
                {
                    uint32_t t, due;
                    asm volatile("mov.u32 %0, %%clock;" : "=r"(due) :: "memory");
                    due += (PACE * (u0 - p.c0)) / step;
                    for (; __any_sync(~0u, u0 < fe0); u0 += step, due += PACE) {
                        do { asm volatile("mov.u32 %0, %%clock;" : "=r"(t) :: "memory"); } while (__any_sync(~0u, (int)(t - due) < 0));
                        cell(u0, inf.z & 1);
                    }
                }
                for (int j = XEARLY + rank - 1;; j += 2) {
                    uint4 v; uint32_t ahead;
                    for (int n = 0; __any_sync(~0u, (ahead = (((v = lds128v(tk + ((j & 7) << 4))).x >> 20) - (j + 1)) & 0xFFF) >= 0x800); n++) {
                        if (__any_sync(~0u, lds32v(tk + (((j - 1) & 7) << 4)) == (NO_TILE | (uint32_t)j << 20))) { v.x = NO_TILE; break; }
                        __nanosleep(100); fail_if(n > (1 << 24));
                    }
                    if (__any_sync(~0u, (v.x & NO_TILE) == NO_TILE)) break;
                    j += __reduce_max_sync(~0u, ahead);
                    for (int u = v.w & 0xFFFF; __any_sync(~0u, u < (v.w & 0xFFFF) + (v.w >> 16)); u++) cell(u, (v.x >> 17) & 1);
                }
            } else {
                const uint32_t rtk = HELPER ? tk : mapa(tk, lane < CL ? lane : 0), rfull = HELPER ? bar_full : mapa(bar_full, lane < CL ? lane : 0);
                int s = 0; uint32_t ph = 1;
                uint64_t pol;
                if (!HELPER) asm volatile("createpolicy.fractional.L2::evict_first.b64 %0, 1.0;" : "=l"(pol));
                else asm volatile("createpolicy.fractional.L2::evict_normal.b64 %0, 1.0;" : "=l"(pol));
                auto request = [&](int j, const uint4& t) {
                    const bool valid = t.x != NO_TILE;
                    const CUtensorMap* tm = &maps.x[(t.x >> 14) & 1];
                    mbar_wait(bar_empty + 8 * s, ph);
                    if (__any_sync(~0u, valid)) {
                        const uint32_t dst = sb + OFF_X + s * TILE_BYTES;
                        if (HELPER)
                            asm volatile("{\n.reg .pred p;\nelect.sync _|p, 0xffffffff;\n"
                                         "@p cp.async.bulk.tensor.4d.shared::cluster.global.mbarrier::complete_tx::bytes.L2::cache_hint [%0], [%4, {%6, %7, %6, %6}], [%5], %11;\n"
                                         "@p cp.async.bulk.tensor.4d.shared::cluster.global.mbarrier::complete_tx::bytes.L2::cache_hint [%1], [%4, {%6, %8, %6, %6}], [%5], %11;\n"
                                         "@p cp.async.bulk.tensor.4d.shared::cluster.global.mbarrier::complete_tx::bytes.L2::cache_hint [%2], [%4, {%6, %9, %6, %6}], [%5], %11;\n"
                                         "@p cp.async.bulk.tensor.4d.shared::cluster.global.mbarrier::complete_tx::bytes.L2::cache_hint [%3], [%4, {%6, %10, %6, %6}], [%5], %11;\n}\n"
                                         :: "r"(dst), "r"(dst + 9216), "r"(dst + 2 * 9216), "r"(dst + 3 * 9216), "l"(tm), "r"(bar_full + 8 * s), "r"(0),
                                            "r"(t.y & 0xFFFF), "r"(t.y >> 16), "r"(t.z & 0xFFFF), "r"(t.z >> 16), "l"(pol) : "memory");
                        else
                            asm volatile("{\n.reg .pred p;\nelect.sync _|p, 0xffffffff;\n"
                                         "@p cp.async.bulk.tensor.4d.shared::cluster.global.mbarrier::complete_tx::bytes.multicast::cluster.L2::cache_hint [%0], [%4, {%6, %7, %6, %6}], [%5], %11, %12;\n"
                                         "@p cp.async.bulk.tensor.4d.shared::cluster.global.mbarrier::complete_tx::bytes.multicast::cluster.L2::cache_hint [%1], [%4, {%6, %8, %6, %6}], [%5], %11, %12;\n"
                                         "@p cp.async.bulk.tensor.4d.shared::cluster.global.mbarrier::complete_tx::bytes.multicast::cluster.L2::cache_hint [%2], [%4, {%6, %9, %6, %6}], [%5], %11, %12;\n"
                                         "@p cp.async.bulk.tensor.4d.shared::cluster.global.mbarrier::complete_tx::bytes.multicast::cluster.L2::cache_hint [%3], [%4, {%6, %10, %6, %6}], [%5], %11, %12;\n}\n"
                                         :: "r"(dst), "r"(dst + 9216), "r"(dst + 2 * 9216), "r"(dst + 3 * 9216), "l"(tm), "r"(bar_full + 8 * s), "r"(0),
                                            "r"(t.y & 0xFFFF), "r"(t.y >> 16), "r"(t.z & 0xFFFF), "r"(t.z >> 16), "h"((uint16_t)((1u << CL) - 1)), "l"(pol) : "memory");
                    }
                    if (HELPER) {
                        if (lane == 0) { sts128(tk + ((j & 7) << 4), t); mbar_expect_tx(bar_full + 8 * s, valid ? TILE_BYTES : 0); }
                    } else if (lane < CL) {
                        asm volatile("mbarrier.arrive.expect_tx.shared::cluster.b64 _, [%0], %1;" :: "r"(rfull + 8 * s), "r"(valid ? TILE_BYTES + 16 : 16) : "memory");
                        asm volatile("st.async.weak.shared::cluster.mbarrier::complete_tx::bytes.v4.u32 [%0], {%1, %2, %3, %4}, [%5];"
                                     :: "r"(rtk + ((j & 7) << 4)), "r"(t.x | ((uint32_t)(j + 1) << 20)), "r"(t.y), "r"(t.z), "r"(t.w), "r"(rfull + 8 * s) : "memory");
                    }
                    if (++s == NSLOT) { s = 0; ph ^= 1; }
                };
                if (HELPER) {
#pragma unroll 1
                    for (int j = 0; j < XEARLY; j++) request(j, entry_w(p.ncl + cid + (j >> 1) * (p.ncl + p.nh), j & 1, j & 1, 0));
                    mbar_wait(sb + OFF_PLAN, 0);
                    mbar_wait(sb + OFF_GO, 0);
                    for (int j = XEARLY;; j++) {
                        const uint4 t = lds128v(sb + OFF_TAB + 16 * (j - XEARLY));
                        request(j, t);
                        if (__any_sync(~0u, t.x == NO_TILE)) break;
                    }
                } else {
                    static_assert(XEARLY == 2, "");
                    request(0, e0);
                    request(1, e1);
                    mbar_wait(sb + OFF_PLAN, 0);
                    const uint4 inf = lds128v(sb + OFF_INFO);
                    const unsigned long long plan = inf.x | ((unsigned long long)inf.y << 32);
                    const int side = inf.z & 1, nc = inf.z >> 16;
                    const int nh = helpers(p, plan, side), rm = p.rm[nh], rmo = p.rm[p.nh - nh];
                    const uint32_t ratio = p.ratio[nh], ratioo = p.ratio[p.nh - nh];
                    const int st = NSTAT * nc, sto = NSTAT * (p.ncl - nc);
                    uint4 t = lds128v(sb + OFF_TAB + 16 * ((inf.z >> 8) & 0xFF));
                    mbar_wait(sb + OFF_GO, 0);
                    int j = XEARLY;
#pragma unroll 1
                    for (; j < XEARLY + NSTAT - 2; j++) {
                        const uint4 tn = lds128v(sb + OFF_TAB + 16 * (((inf.z >> 8) & 0xFF) + (j + 1 - XEARLY) * nc));
                        request(j, t);
                        t = tn;
                    }
                    uint32_t drawn = 0;
                    int q = side;
                    request(j++, t);
                    draw(drawn, &g_ticket, 1u << (16 * side));
                    t = lds128v(sb + OFF_TAB + 16 * (((inf.z >> 8) & 0xFF) + (NSTAT - 1) * nc));
                    mbar_wait(sb + OFF_PLAN2, 0);
                    for (;; j++) {
                        request(j, t);
                        uint32_t v = __reduce_max_sync(~0u, drawn);
                        int m = st + ((v >> (16 * side)) & 0xFFFF), mo = sto + ((v >> (16 - 16 * side)) & 0xFFFF);
                        if (q == side ? m >= rm && mo < rmo : mo >= rmo && m < rm) {
                            q ^= 1;
                            draw(drawn, &g_ticket, 1u << (16 * q));
                            v = __reduce_max_sync(~0u, drawn);
                            m = st + ((v >> (16 * side)) & 0xFFFF); mo = sto + ((v >> (16 - 16 * side)) & 0xFFFF);
                        }
                        if (q == side ? m >= rm : mo >= rmo) break;
                        const bool own = q == side;
                        q = m + ((m * ratio) >> 16) > mo + ((mo * ratioo) >> 16) + DELTA ? side ^ 1 : side;
                        draw(drawn, &g_ticket, 1u << (16 * q));
                        if (own) t = lds128v(sb + OFF_TAB + 16 * m);
                        else t = cl_entry(p, mo, side ^ 1, ratioo, plan);
                    }
                    t.x = NO_TILE;
                    request(j + 1, t);
                    if (lane == 0 && atomicInc(&g_done, p.ncl - 1) == (uint32_t)p.ncl - 1) g_ticket = 0;
                }
            }
        } else {
            const int g = warp - 13;
            uint64_t spol;
            asm volatile("createpolicy.fractional.L2::evict_first.b64 %0, 1.0;" : "=l"(spol));
            mbar_wait(sb + OFF_GO, 0);
            if (g == 2 && lane == 0 && atomicInc(&g_passed, p.nctas - 1) == (uint32_t)p.nctas - 1) {
#pragma unroll
                for (int m = 0; m < 9; m++) g_ready[m * 32] = 0;
                g_plan = make_ulonglong2(0, 0);
            }
            __syncwarp();
            for (int i = 0;; i++) {
                asm volatile("bar.arrive %0, 160;" :: "r"(12 + g) : "memory");
                asm volatile("bar.sync %0, 160;" :: "r"(1 + g) : "memory");
                const uint4 t = lds128v(tk + ((i & 7) << 4));
                if ((t.x & NO_TILE) == NO_TILE) break;
                const CUtensorMap* tm = &maps.o[(t.x >> 14) & 1];
                const int row[4] = {(int)(t.y & 0xFFFF), (int)(t.y >> 16), (int)(t.z & 0xFFFF), (int)(t.z >> 16)};
                if (lane == 0) {
#pragma unroll
                    for (int k = 0; k < 4; k++)
                        asm volatile("cp.async.bulk.tensor.3d.global.shared::cta.bulk_group.L2::cache_hint [%0, {%2, %3, %4}], [%1], %5;"
                                     :: "l"(tm), "r"(sb + OFF_STG + g * STG_BYTES + k * 1024), "r"((g * 3 + rank) * 64), "r"(row[k]), "r"(0), "l"(spol) : "memory");
                    asm volatile("cp.async.bulk.commit_group;" ::: "memory");
                    asm volatile("cp.async.bulk.wait_group.read 0;" ::: "memory");
                }
                __syncwarp();
            }
        }
        __syncwarp();
        if (!HELPER) asm volatile("barrier.cluster.arrive.relaxed.aligned;\nbarrier.cluster.wait.aligned;" ::: "memory");
    } else {
        asm volatile("setmaxnreg.inc.sync.aligned.u32 160;");
        const int wg = warp >> 2, wtid = tid & 127, r = lane >> 2;
        if (HELPER) asm volatile("bar.sync 0;" ::: "memory");
        else {
            int prb = cid;
            if (prb >= 36) asm volatile("barrier.cluster.wait.aligned;" ::: "memory");
#pragma unroll 1
            for (int round = 0; prb < 36; prb += p.ncl, round++) {
                const uint32_t wsm = sb + OFF_WST, msk = sb + OFF_MSK + (round & 1) * 288, mbar = sb + OFF_MBAR + (round & 1) * 8;
                if (round) {
                    asm volatile("bar.sync 3, 384;" ::: "memory");
                    if (tid == 0) mbar_expect_tx(mbar, 36 * 8);
                    prep_load(prb >> 2);
                }
                const int nt = ties(wv[0].x, wv[1].x, wv[2].x, wv[3].x) + ties(wv[0].y, wv[1].y, wv[2].y, wv[3].y) +
                               ties(wv[0].z, wv[1].z, wv[2].z, wv[3].z) + ties(wv[0].w, wv[1].w, wv[2].w, wv[3].w);
                const uint32_t mk = __ballot_sync(~0u, nt > 0), md = __ballot_sync(~0u, nt > 1);
                if (round == 0) asm volatile("barrier.cluster.wait.aligned;" ::: "memory");
                if (lane < CL)
                    asm volatile("st.async.weak.shared::cluster.mbarrier::complete_tx::bytes.v2.u32 [%0], {%1, %2}, [%3];"
                                 :: "r"(mapa(msk + (rank * 12 + warp) * 8, lane)), "r"(mk), "r"(md), "r"(mapa(mbar, lane)) : "memory");
#pragma unroll
                for (int j = 0; j < 4; j++) {
                    const int row = wrow + j;
                    const uint32_t ad = wsm + row * 128 + (((lane >> 2) ^ ((row & 1) | ((row >> 1) & 6))) << 4);
                    asm volatile("st.shared.v4.b32 [%0], {%1,%2,%3,%4};" :: "r"(ad), "r"(wv[j].x), "r"(wv[j].y), "r"(wv[j].z), "r"(wv[j].w) : "memory");
                }
                if (warp >= 6) asm volatile("bar.arrive 1, 384;" ::: "memory");
                else {
                    asm volatile("bar.sync 1, 384;" ::: "memory");
                    mbar_wait(mbar, (round >> 1) & 1);
                    uint4 ms = make_uint4(0, 0, 0, 0);
                    if (lane < KSTEPS) ms = lds128v(msk + 16 * lane);
                    const uint32_t m0 = ms.x, m1 = ms.z;
                    uint32_t c0 = m0 - ((m0 >> 1) & 0x55555555u), c1 = m1 - ((m1 >> 1) & 0x55555555u);
                    c0 = (c0 & 0x33333333u) + ((c0 >> 2) & 0x33333333u) + (c1 & 0x33333333u) + ((c1 >> 2) & 0x33333333u);
                    c1 = __reduce_add_sync(~0u, (c0 >> 4) & 0x0F0F0F0Fu); c0 = __reduce_add_sync(~0u, c0 & 0x0F0F0F0Fu);
                    auto key = [&](int v) { return ((((v & 1) ? c1 : c0) >> (4 * (v & 6))) & 0xFFu) * 8 + v; };
                    const uint32_t ku = key(lane & 7);
                    int rk = (key(2 * (lane >> 3)) < ku) + (key(2 * (lane >> 3) + 1) < ku);
                    rk += __shfl_xor_sync(~0u, rk, 8); rk += __shfl_xor_sync(~0u, rk, 16);
                    auto bits = [&](uint32_t a, uint32_t b, int u) { return ((a >> (4 * u)) & 15u) | (((b >> (4 * u)) & 15u) << 4); };
                    int ulo = 0, uhi = 0, cnt[4]; uint32_t md = 0;
#pragma unroll
                    for (int z = 0; z < 4; z++) {
                        const int ua = __ffs(__ballot_sync(~0u, rk == z)) - 1, ub = __ffs(__ballot_sync(~0u, rk == 7 - z)) - 1;
                        const uint32_t ta = bits(m0, m1, ua), tb = bits(m0, m1, ub), v = ta | tb | ((ta & tb) | bits(ms.y, ms.w, ua) | bits(ms.y, ms.w, ub)) << 8;
                        cnt[z] = __popc(v);
                        if (z == (prb & 3)) { ulo = ua; uhi = ub; md = v; }
                    }
                    const uint32_t l01 = __reduce_add_sync(~0u, cnt[0] | cnt[1] << 16), l23 = __reduce_add_sync(~0u, cnt[2] | cnt[3] << 16);
                    const int full = max(max(max((int)(l01 & 0xFFFF) - cnt[0], (int)(l01 >> 16) - cnt[1]), max((int)(l23 & 0xFFFF) - cnt[2], (int)(l23 >> 16) - cnt[3])), 16);
                    const int twice = __reduce_min_sync(~0u, lane < KSTEPS ? full << 12 | (64 - cnt[0] - cnt[1] - cnt[2] - cnt[3]) << 5 | lane : 0x7FFFFFFF) & 31;
                    if (lane == twice) md = 0;
                    uint32_t lo[4], hi[4];
                    load_unit(wsm, warp, ulo, lane, lo); load_unit(wsm, warp, uhi, lane, hi);
                    const uint2 bias2 = make_uint2(__shfl_sync(~0u, ulo < 4 ? b0 : b1, (ulo * 8 + r) & 31) * 0x10001u, __shfl_sync(~0u, uhi < 4 ? b0 : b1, (uhi * 8 + r) & 31) * 0x10001u);
                    emit_step(lo, hi, md, prb, rank * 6 + warp, lane, ulo | (uhi << 4) | (twice << 8), bias2, rank * 6 + warp == twice);
                    asm volatile("bar.sync 2, 192;" ::: "memory");
                    if (tid == 0) asm volatile("red.release.gpu.global.add.u32 [%0], 1;" :: "l"(&g_ready[(prb >> 2) * 32]) : "memory");
                }
            }
            if (warp == 0 && lane < CL) mbar_arrive_cluster(mapa(sb + OFF_GO, lane));
        }
        const int mt = wg * 3 + rank, rb = mt * 4 + (warp & 3);
        if ((warp & 3) == 0) {
            uint32_t v; int n = 0;
            do { asm volatile("ld.acquire.gpu.global.u32 %0, [%1];" : "=r"(v) : "l"(&g_ready[mt * 32]) : "memory"); fail_if(++n > (1 << 22)); } while (__any_sync(~0u, v < 4 * CL));
        }
        asm volatile("bar.sync %0, 128;" :: "r"(12 + wg) : "memory");
        if (wg > 0) asm volatile("bar.sync %0, 256;" :: "r"(7 + wg) : "memory");
        uint32_t a[KSTEPS + 1][4], meta[9];
        uint2 rv[3]; uint32_t ro[3], sel[3];
        uint32_t info, bias_lo, bias_hi;
        {
            const uint4* ap = g_aux + rb * 6 * 32 + lane;
            const uint4 v3 = ldw(ap + 96), v2 = ldw(ap + 64), v4 = ldw(ap + 128), v5 = ldw(ap + 160), v0 = ldw(ap), v1 = ldw(ap + 32);
            meta[0] = v0.x; meta[1] = v0.y; meta[2] = v0.z; meta[3] = v0.w; meta[4] = v1.x; meta[5] = v1.y; meta[6] = v1.z; meta[7] = v1.w;
            meta[8] = v2.x; info = v2.y; bias_lo = v2.z; bias_hi = v2.w;
            ro[0] = v3.x; ro[1] = v3.y; ro[2] = v3.z;
            rv[0] = make_uint2(v4.x, v4.y); rv[1] = make_uint2(v4.z, v4.w); rv[2] = make_uint2(v5.x, v5.y);
        }
#pragma unroll
        for (int k = 0; k < KSTEPS + 1; k++) { uint4 v = ldw(&g_afrag[(mt * (KSTEPS + 1) + k) * 128 + wtid]); a[k][0] = v.x; a[k][1] = v.y; a[k][2] = v.z; a[k][3] = v.w; }
        if (wg < 2) asm volatile("bar.arrive %0, 256;" :: "r"(8 + wg) : "memory");
        if (lane == 0) mbar_arrive(sb + OFF_GO);
        auto selector = [](uint32_t o) { return 0x5410u + ((o >> 15) & 1) * 0x22u + (o >> 31) * 0x2200u; };
#pragma unroll
        for (int j = 0; j < 3; j++) { sel[j] = selector(ro[j]); ro[j] &= 0x7FFF7FFFu; }
        mbar_wait(bar_full, 0);
        info = __shfl_sync(~0u, info, 0);
        const int ngrp = info & 0xFF, ulo = (info >> 8) & 7, uhi = (info >> 12) & 7;
        const uint32_t stg = sb + OFF_STG + wg * STG_BYTES + ((lane >> 4) * 8 + (lane & 7)) * 128 + (((((lane >> 3) & 1) ? uhi : ulo) ^ (lane & 7)) << 4);
        const uint32_t twice = (((info >> 17) & 15) * 1024 + ((info >> 16) & 1) * 64) >> 4;
        const uint32_t rempty = HELPER ? bar_empty : mapa(bar_empty, 0);
        float acc[NACC];
        uint32_t bq[NB][6];
        auto gather = [&](uint32_t xb) {
#pragma unroll
            for (int j = 0; j < 4; j++) {
                const uint32_t o = xb + ((j & 1) ? ro[j >> 1] >> 16 : ro[j >> 1] & 0xFFFF);
#pragma unroll
                for (int n = 0; n < NB; n++) {
                    bq[n][j] = 0;
                    asm volatile("{\n.reg .pred p;\nsetp.lt.s32 p, %2, %3;\n@p ld.shared.b32 %0, [%1];\n}" : "+r"(bq[n][j]) : "r"(o + n * 9216), "r"(j), "r"(ngrp) : "memory");
                }
            }
        };
        auto select = [&]() {
#pragma unroll
            for (int n = 0; n < NB; n++)
#pragma unroll
                for (int j = 0; j < 2; j++) bq[n][2 * j] = __byte_perm(bq[n][2 * j], bq[n][2 * j + 1], sel[j]);
        };
        auto further = [&](uint32_t xb, int bar) {
#pragma unroll 1
            for (int y = 4; y < min(ngrp, 5); y++) {
#pragma unroll
                for (int n = 0; n < NB; n++) { bq[n][4] = lds32(xb + (ro[2] & 0xFFFF) + n * 9216); bq[n][5] = lds32(xb + (ro[2] >> 16) + n * 9216); }
#pragma unroll
                for (int n = 0; n < NB; n++) mma_k8(acc + 4 * n, rv[2], __byte_perm(bq[n][4], bq[n][5], sel[2]));
                if (bar >= 0) asm volatile("bar.arrive %0, 256;" :: "r"(bar) : "memory");
#pragma unroll 1
                for (int z = 3; 2 * z < ngrp; z++) {
                    const uint2 v = __ldca(&g_rval[(rb * 36 + z) * 32 + lane]); const uint32_t off = __ldca(&g_roff[(rb * 36 + z) * 32 + lane]);
                    uint32_t bx[NB];
#pragma unroll
                    for (int n = 0; n < NB; n++) bx[n] = __byte_perm(lds32(xb + (off & 0x7FFF) + n * 9216), lds32(xb + ((off >> 16) & 0x7FFF) + n * 9216), selector(off));
#pragma unroll
                    for (int n = 0; n < NB; n++) mma_k8(acc + 4 * n, v, bx[n]);
                }
            }
        };
        bool more = true;
#pragma unroll
        for (int n = 0; n < NB; n++) bq[n][4] = bq[n][5] = 0;
        gather(sb + OFF_X);
        select();
#pragma unroll
        for (int n = 0; n < NB; n++) mma_k16(acc + 4 * n, rv[0], rv[1], bq[n][0], bq[n][2], 0.f, 0.f, 0.f, 0.f);
        further(sb + OFF_X, -1);
        const int bar_a = 8 + wg, bar_an = 8 + (wg + 2) % 3, bar_tn = 4 + (wg + 2) % 3;
        if (wg == 1) asm volatile("bar.arrive 4, 256;" ::: "memory");
        if (wg == 2) { asm volatile("bar.sync 10, 256;" ::: "memory"); asm volatile("bar.arrive 5, 256;" ::: "memory"); }
        int s = 0; uint32_t ph = 0;
        bool ready = false;
        for (int i = 0; more; i++) {
            const uint32_t xb = sb + OFF_X + s * TILE_BYTES;
            const int s1 = s + 1 == NSLOT ? 0 : s + 1;
            const uint32_t ph1 = s1 == 0 ? ph ^ 1 : ph;
            asm volatile("bar.sync %0, 256;" :: "r"(4 + wg) : "memory");
            const uint64_t desc = ((uint64_t)1 << 62) | ((uint64_t)(9216 >> 4) << 32) | ((uint64_t)1 << 16) | (uint64_t)(xb >> 4);
            asm volatile("wgmma.fence.sync.aligned;" ::: "memory");
#pragma unroll
            for (int k = 0; k < KSTEPS; k++) {
                const uint64_t d = desc + (uint64_t)(((k >> 1) * 1024 + (k & 1) * 64) >> 4);
                if (k & 1) wgmma_sp<1>(acc, a[k], d, meta[k >> 1]);
                else       wgmma_sp<0>(acc, a[k], d, meta[k >> 1]);
            }
            wgmma_sp<0>(acc, a[KSTEPS], desc + twice, 0x44444444u);
            asm volatile("wgmma.commit_group.sync.aligned;" ::: "memory");
            asm volatile("bar.arrive %0, 256;" :: "r"(bar_an) : "memory");
            if (!ready) mbar_wait(bar_full + 8 * s1, ph1);
            const uint32_t tn = lds32v(tk + (((i + 1) & 7) << 4));
            gather(sb + OFF_X + s1 * TILE_BYTES);
            asm volatile("bar.sync %0, 160;" :: "r"(12 + wg) : "memory");
            asm volatile("wgmma.wait_group.sync.aligned 0;" ::: "memory");
            if (wtid == 0) { if (HELPER) mbar_arrive(bar_empty + 8 * s); else mbar_arrive_cluster(rempty + 8 * s); }
#pragma unroll
            for (int n = 0; n < NB; n += 2) {
                const uint32_t p0 = pack_bias(acc[4 * n], acc[4 * n + 1], bias_lo), p1 = pack_bias(acc[4 * n + 2], acc[4 * n + 3], bias_hi);
                const uint32_t p2 = pack_bias(acc[4 * n + 4], acc[4 * n + 5], bias_lo), p3 = pack_bias(acc[4 * n + 6], acc[4 * n + 7], bias_hi);
                if (n == 0) asm volatile("stmatrix.sync.aligned.m8n8.x4.trans.shared.b16 [%0], {%1,%2,%3,%4};" :: "r"(stg + n * 1024), "r"(p0), "r"(p1), "r"(p2), "r"(p3) : "memory");
                else asm volatile("{\n.reg .pred p;\nAGAIN:\nstmatrix.sync.aligned.m8n8.x4.trans.shared.b16 [%0], {%1,%2,%3,%4};\nsetp.eq.u32 p, %5, 0xFFFFFFFE;\n@p bra.uni AGAIN;\n}"
                                  :: "r"(stg + n * 1024), "r"(p0), "r"(p1), "r"(p2), "r"(p3), "r"(info) : "memory");
            }
            more = __any_sync(~0u, (tn & NO_TILE) != NO_TILE);
            select();
            if (wg != 2 || more) {
                asm volatile("{\n.reg .pred p;\nTURN:\nbar.sync %0, 256;\nsetp.eq.u32 p, %1, 0xFFFFFFFF;\n@p bra.uni TURN;\n}" :: "r"(bar_a), "r"(info) : "memory");
#pragma unroll
                for (int n = 0; n < NB; n++) {
                    mma_k16(acc + 4 * n, rv[0], rv[1], bq[n][0], bq[n][2], 0.f, 0.f, 0.f, 0.f);
                    if (n == 0) asm volatile("{\n.reg .pred p;\nsetp.le.s32 p, %1, 4;\n@p bar.arrive %0, 256;\n}" :: "r"(bar_tn), "r"(ngrp) : "memory");
                }
                further(sb + OFF_X + s1 * TILE_BYTES, bar_tn);
            }
            asm volatile("fence.proxy.async.shared::cta;" ::: "memory");
            asm volatile("bar.arrive %0, 160;" :: "r"(1 + wg) : "memory");
            s = s1; ph = ph1;
            ready = __all_sync(~0u, mbar_test(bar_full + 8 * (s + 1 == NSLOT ? 0 : s + 1), s + 1 == NSLOT ? ph ^ 1 : ph));
        }
        if (wg == 0) asm volatile("bar.sync 4, 256;" ::: "memory");
        asm volatile("bar.sync %0, 160;" :: "r"(12 + wg) : "memory");
        asm volatile("bar.arrive %0, 160;" :: "r"(1 + wg) : "memory");
        if (!HELPER) asm volatile("barrier.cluster.arrive.relaxed.aligned;\nbarrier.cluster.wait.aligned;" ::: "memory");
    }
}

typedef CUresult (*EncodeFn)(CUtensorMap*, CUtensorMapDataType, cuuint32_t, void*, const cuuint64_t*, const cuuint64_t*, const cuuint32_t*, const cuuint32_t*,
                             CUtensorMapInterleave, CUtensorMapSwizzle, CUtensorMapL2promotion, CUtensorMapFloatOOBfill);

__global__ void plain_kernel(const __nv_bfloat16* x, const __nv_bfloat16* w, const __nv_bfloat16* b, __nv_bfloat16* out, int ntok) {
    const int t0 = blockIdx.x * 8;
    for (int f = threadIdx.x; f < D; f += blockDim.x) {
        float acc[8] = {};
        for (int g = 0; g < D / 4; g++) {
            float v[4], m[4];
            for (int i = 0; i < 4; i++) { v[i] = __bfloat162float(w[(4 * g + i) * D + f]); m[i] = fabsf(v[i]); }
            const float thr = fmaxf(fminf(fmaxf(m[0], m[1]), fmaxf(m[2], m[3])), fmaxf(fminf(m[0], m[1]), fminf(m[2], m[3])));
            for (int i = 0; i < 4; i++)
                for (int t = 0; t < 8; t++)
                    if (m[i] >= thr && t0 + t < ntok) acc[t] += v[i] * __bfloat162float(x[(size_t)(t0 + t) * D + 4 * g + i]);
        }
        for (int t = 0; t < 8; t++)
            if (t0 + t < ntok) out[(size_t)(t0 + t) * D + f] = __hadd(__float2bfloat16(acc[t]), b[f]);
    }
}

extern "C" void kernel_launch(void* const* d_in, const int* in_sizes, int n_in, void* d_out, int out_size) {
    static EncodeFn enc = nullptr;
    static int ncl = 0, nhelp = 0;
    const int ntok = in_sizes[0] / D;
    cudaLaunchConfig_t cfg = {};
    cudaLaunchAttribute at[1];
    at[0].id = cudaLaunchAttributeClusterDimension; at[0].val.clusterDim.x = CL; at[0].val.clusterDim.y = 1; at[0].val.clusterDim.z = 1;
    cfg.blockDim = dim3(NTHREADS); cfg.dynamicSmemBytes = SMEM_BYTES; cfg.attrs = at; cfg.numAttrs = 1; cfg.stream = cudaStreamPerThread;
    if (!enc) {
        cudaDriverEntryPointQueryResult qr; void* fn = nullptr;
        cudaGetDriverEntryPoint("cuTensorMapEncodeTiled", &fn, cudaEnableDefault, &qr);
        enc = (EncodeFn)fn;
        cudaFuncSetAttribute(spgemm_kernel<false>, cudaFuncAttributeMaxDynamicSharedMemorySize, SMEM_BYTES);
        cudaFuncSetAttribute(spgemm_kernel<true>, cudaFuncAttributeMaxDynamicSharedMemorySize, SMEM_BYTES);
        int dev = 0, nsm = 0;
        cudaGetDevice(&dev);
        cudaDeviceGetAttribute(&nsm, cudaDevAttrMultiProcessorCount, dev);
        cfg.gridDim = dim3(CL * (nsm / CL));
        cudaOccupancyMaxActiveClusters(&ncl, spgemm_kernel<false>, &cfg);
        if (ncl < 1) ncl = 1;
        nhelp = nsm > CL * ncl ? (nsm - CL * ncl) / CL : 0;
        if (nhelp > 7) nhelp = 7;
    }
    if (ntok % 4096 || ntok < 16384 || ntok > 65536 || ncl < 2 || ncl > 56 || 8 * (ncl + nhelp) > ntok / 64) {
        plain_kernel<<<(ntok + 7) / 8, 192, 0, cudaStreamPerThread>>>((const __nv_bfloat16*)d_in[0], (const __nv_bfloat16*)d_in[1], (const __nv_bfloat16*)d_in[2], (__nv_bfloat16*)d_out, ntok);
        return;
    }
    Maps maps;
    for (int v = 0; v < 2; v++) {
        const cuuint32_t rows = v == 0 ? 2 : 1;
        const cuuint64_t pitch = (v == 0 ? 14 : 57) * D * 2;
        {
            cuuint64_t dims[4] = {64, (cuuint64_t)ntok, 8 / rows, 9};
            cuuint64_t strides[3] = {D * 2, pitch, 128};
            cuuint32_t box[4] = {64, rows, 8 / rows, 9}, es[4] = {1, 1, 1, 1};
            enc(&maps.x[v], CU_TENSOR_MAP_DATA_TYPE_BFLOAT16, 4, d_in[0], dims, strides, box, es, CU_TENSOR_MAP_INTERLEAVE_NONE,
                CU_TENSOR_MAP_SWIZZLE_128B, CU_TENSOR_MAP_L2_PROMOTION_L2_128B, CU_TENSOR_MAP_FLOAT_OOB_FILL_NONE);
        }
        {
            cuuint64_t dims[3] = {D, (cuuint64_t)ntok, 8 / rows};
            cuuint64_t strides[2] = {D * 2, pitch};
            cuuint32_t box[3] = {64, rows, 8 / rows}, es[3] = {1, 1, 1};
            enc(&maps.o[v], CU_TENSOR_MAP_DATA_TYPE_BFLOAT16, 3, d_out, dims, strides, box, es, CU_TENSOR_MAP_INTERLEAVE_NONE,
                CU_TENSOR_MAP_SWIZZLE_128B, CU_TENSOR_MAP_L2_PROMOTION_NONE, CU_TENSOR_MAP_FLOAT_OOB_FILL_NONE);
        }
    }
    {
        cuuint64_t dims[3] = {256, (cuuint64_t)ntok * D * 2 / 2048, 4};
        cuuint64_t strides[2] = {2048, 16384};
        cuuint32_t box[3] = {256, 4, 4}, es[3] = {1, 1, 1};
        enc(&maps.pf, CU_TENSOR_MAP_DATA_TYPE_FLOAT64, 3, d_in[0], dims, strides, box, es, CU_TENSOR_MAP_INTERLEAVE_NONE,
            CU_TENSOR_MAP_SWIZZLE_NONE, CU_TENSOR_MAP_L2_PROMOTION_NONE, CU_TENSOR_MAP_FLOAT_OOB_FILL_NONE);
    }
    Params p;
    p.w = (const uint16_t*)d_in[1]; p.bias = (const uint16_t*)d_in[2]; p.x = (const uint8_t*)d_in[0];
    p.nq = ntok / 64; p.npages = (int)(((size_t)ntok * D * 2) >> 21);
    const int nc = ncl, nh = nhelp;
    p.ncl = nc; p.nh = nh; p.nctas = CL * (nc + nh);
    p.m0 = (nc + nh) * XEARLY / 2;
    for (int h = 0; h < 8; h++) {
        const uint32_t R = p.nq - p.m0, H = h * (HT * p.nq / 1024 * 44 / (nc + nh));
        p.ratio[h] = h <= nh ? (H << 16) / (R - H) : 0;
        p.rm[h] = p.ratio[h] ? (((R - 1) << 16) + 0x7FFFu) / (0x10000u + p.ratio[h]) + 1 : R;
    }
    p.c0 = (p.m0 * 9) >> 3;
    p.tb = p.m0 + (NSLOT - XEARLY) * (nc + nh) / 2;
    p.ta = p.tb + 1 + (int)((p.nq - p.tb) * TAFRAC); p.te = (int)(p.nq * TEFRAC) + 2;
    p.slope0 = ((LEAD1 - LEAD0) << 16) / (p.ta - p.tb); p.slope1 = ((LEAD1 - LEADE) << 16) / (p.te - p.ta);
    cfg.gridDim = dim3(CL * nc);
    cudaLaunchKernelEx(&cfg, spgemm_kernel<false>, p, maps);
    if (nh) {
        at[0].id = cudaLaunchAttributeProgrammaticStreamSerialization; at[0].val.programmaticStreamSerializationAllowed = 1;
        cfg.gridDim = dim3(CL * nh);
        cudaLaunchKernelEx(&cfg, spgemm_kernel<true>, p, maps);
    }
}
```

```cpp
#include <cuda_runtime.h>
#include <cuda_bf16.h>
#include <cuda.h>
#include <stdint.h>

constexpr int D = 576;
constexpr int NT = 32;
constexpr int NSLOT = 5;
constexpr int XEARLY = 2;
constexpr int NSTAT = 4;
constexpr int DELTA = 24;
constexpr int HT = 44;
constexpr int LEAD0 = 140, LEAD1 = 310, LEADE = 40, PACE = 1200;
constexpr double TAFRAC = 0.249, TEFRAC = 0.97;
constexpr int NPR = 2, PWAIT = 1200;
constexpr int KSTEPS = 18;
constexpr int CL = 3;
constexpr int TILE_BYTES = NT * D * 2;
constexpr int STG_BYTES = NT * 128;
constexpr int NACC = NT / 2;
constexpr int NB = NT / 8;
constexpr int NCONS = 384;
constexpr int NTHREADS = 512;
constexpr int NTAB = 1024;
constexpr uint32_t NO_TILE = 0xFFFFFu;

constexpr int OFF_X = 0;
constexpr int OFF_WST = OFF_X + (NSLOT - 1) * TILE_BYTES;
constexpr int OFF_STG = OFF_X + NSLOT * TILE_BYTES;
constexpr int OFF_TAB = OFF_STG + 3 * STG_BYTES;
constexpr int OFF_TK = OFF_TAB + 16 * NTAB;
constexpr int OFF_MSK = OFF_TK + 128;
constexpr int OFF_INFO = OFF_MSK + 2 * 36 * 8;
constexpr int OFF_FULL = OFF_INFO + 32;
constexpr int OFF_EMPTY = OFF_FULL + 8 * NSLOT;
constexpr int OFF_MBAR = OFF_EMPTY + 8 * NSLOT;
constexpr int OFF_GO = OFF_MBAR + 16;
constexpr int OFF_PLAN = OFF_GO + 8;
constexpr int OFF_PLAN2 = OFF_PLAN + 8;
constexpr int SMEM_BYTES = OFF_PLAN2 + 8 + 1024;
static_assert(SMEM_BYTES <= 232448 && TILE_BYTES >= 192 * 128 && XEARLY % 2 == 0 && XEARLY < NSLOT && NSLOT < 8 && NB == 4 && OFF_INFO % 16 == 0, "layout");

__device__ __align__(128) uint4    g_afrag[9 * (KSTEPS + 1) * 128];
__device__ __align__(128) uint4    g_aux[36 * 6 * 32];
__device__ __align__(128) uint2    g_rval[36 * 36 * 32];
__device__ __align__(128) uint32_t g_roff[36 * 36 * 32];
__device__ __align__(128) uint32_t g_ready[9 * 32];
__device__ __align__(128) uint32_t g_passed;
__device__ __align__(128) uint32_t g_ticket;
__device__ __align__(128) uint32_t g_done;
__device__ __align__(128) ulonglong2 g_plan;

__device__ __forceinline__ uint32_t max2(uint32_t a, uint32_t b) { uint32_t d; asm("max.u16x2 %0, %1, %2;" : "=r"(d) : "r"(a), "r"(b)); return d; }
__device__ __forceinline__ uint32_t min2(uint32_t a, uint32_t b) { uint32_t d; asm("min.u16x2 %0, %1, %2;" : "=r"(d) : "r"(a), "r"(b)); return d; }
__device__ __forceinline__ uint32_t sign2(uint32_t a) { uint32_t d; asm("prmt.b32 %0, %1, %1, 0xBB99;" : "=r"(d) : "r"(a)); return d; }
__device__ __forceinline__ void load_unit(uint32_t wsm, int ls, int unit, int lane, uint32_t (&m)[4]) {
    const int row = ls * 32 + (lane >> 4) * 16 + ((lane & 7) >> 1) * 4 + ((lane >> 3) & 1) * 2 + (lane & 1);
    const uint32_t ad = wsm + row * 128 + ((unit ^ ((row & 1) | ((row >> 1) & 6))) << 4);
    asm volatile("ldmatrix.sync.aligned.m8n8.x4.trans.shared.b16 {%0,%1,%2,%3}, [%4];" : "=r"(m[0]), "=r"(m[1]), "=r"(m[2]), "=r"(m[3]) : "r"(ad) : "memory");
}
__device__ __forceinline__ void zip4(uint32_t a01, uint32_t a23, uint32_t b01, uint32_t b23, uint32_t (&x)[4]) {
    x[0] = __byte_perm(a01, b01, 0x5410); x[1] = __byte_perm(a01, b01, 0x7632); x[2] = __byte_perm(a23, b23, 0x5410); x[3] = __byte_perm(a23, b23, 0x7632);
}
__device__ __forceinline__ void middle2(const uint32_t (&x)[4], uint32_t (&m)[4], uint32_t& u, uint32_t& v) {
#pragma unroll
    for (int i = 0; i < 4; i++) m[i] = x[i] & 0x7FFF7FFFu;
    u = min2(max2(m[0], m[1]), max2(m[2], m[3])); v = max2(min2(m[0], m[1]), min2(m[2], m[3]));
}
__device__ __forceinline__ int ties(uint32_t x0, uint32_t x1, uint32_t x2, uint32_t x3) {
    const uint32_t x[4] = {x0, x1, x2, x3};
    uint32_t m[4], u, v;
    middle2(x, m, u, v);
    const uint32_t t = u ^ v, f = u ^ min2(min2(m[0], m[1]), min2(m[2], m[3]));
    const bool t0 = (t & 0xFFFFu) == 0 && (v & 0xFFFFu) != 0, t1 = t < 0x10000u && v >= 0x10000u;
    return t0 + t1 + 2 * ((t0 && (f & 0xFFFFu) == 0) || (t1 && f < 0x10000u));
}
__device__ __forceinline__ void split(const uint32_t (&x)[4], bool dbl, bool P, uint32_t& alo, uint32_t& ahi, uint32_t& nib, uint32_t& va, uint32_t& vb) {
    uint32_t m[4], u, v;
    middle2(x, m, u, v);
    const uint32_t c = 0x80008000u - max2(max2(u, v), 0x00010001u);
    uint32_t k0 = sign2(m[0] + c), k1 = sign2(m[1] + c), k2 = sign2(m[2] + c), k3 = sign2(m[3] + c);
    const uint32_t three = (k0 & k1 & (k2 | k3)) | (k2 & k3 & (k0 | k1)), four = k0 & k1 & k2 & k3;
    const bool a2 = !dbl && P;
    const uint32_t pa = a2 ? k2 : k0, pb = dbl ? k2 : P ? k3 : k1;
    const uint32_t ra = three & pa, rb = three & pb & (four | ~pa);
    va = (a2 ? x[2] : x[0]) & ra; vb = (dbl ? x[2] : P ? x[3] : x[1]) & rb;
    if (a2) k2 &= ~ra; else k0 &= ~ra;
    if (dbl) k2 &= ~rb; else if (P) k3 &= ~rb; else k1 &= ~rb;
    const uint32_t s1 = k1 & k0, s2 = k2 & (k0 | k1);
    const uint32_t t = (k1 & x[1]) | (~k1 & k2 & x[2]);
    const uint32_t x0 = (k0 & x[0]) | (~k0 & t), x1 = (s1 & x[1]) | (s2 & x[2]) | (k3 & x[3]);
    nib = (~k0 & k1 & 0x00010001u) | (~k0 & ~k1 & 0x00020002u) | (~s2 & 0x00040004u) | (~s1 & 0x00080008u);
    alo = __byte_perm(x0, x1, 0x5410); ahi = __byte_perm(x0, x1, 0x7632);
}
__device__ __forceinline__ uint32_t resid_off(int g, int P, int r) {
    int k0 = 4 * g + 2 * P;
    int chunk = k0 >> 6, byte = (k0 & 63) * 2;
    return chunk * 1024 + r * 128 + (((byte >> 4) ^ r) << 4) + (byte & 15);
}
__device__ __forceinline__ void emit_step(const uint32_t (&lo)[4], const uint32_t (&hi)[4], uint32_t md, int rb, int ks, int lane, uint32_t units, uint2 bias2, bool twice) {
    uint32_t* const aux = (uint32_t*)(g_aux + rb * 6 * 32);
    auto put_slot = [&](int j, int ln, uint32_t v, uint32_t off) {
        uint16_t* o = j < 6 ? (uint16_t*)aux + (3 * 32 + ln) * 8 + j : (uint16_t*)g_roff + ((rb * 36 + (j >> 1)) * 32 + ln) * 2 + (j & 1);
        uint16_t* w = j < 6 ? (uint16_t*)aux + ((4 + (j >> 2)) * 32 + ln) * 8 + (j & 2) * 2 + (j & 1) : (uint16_t*)g_rval + ((rb * 36 + (j >> 1)) * 32 + ln) * 4 + (j & 1);
        o[0] = (uint16_t)off; w[0] = (uint16_t)v; w[2] = (uint16_t)(v >> 16);
    };
    const int r = lane >> 2, q = lane & 3, g0 = ks * 8 + q;
    const uint32_t gm = __shfl_sync(~0u, md, ks);
    const uint32_t c2 = __popc(md & 0x5555u) | (__popc(md & 0xAAAAu) << 16);
    const uint32_t tot = __reduce_add_sync(~0u, c2), pre = __reduce_add_sync(~0u, lane < ks ? c2 : 0u);
    const int ne = tot & 0xFFFF, no = tot >> 16;
    const uint32_t par = (q & 1) ? 0xAAAAu : 0x5555u;
    const int base = (q & 1) ? pre >> 16 : pre & 0xFFFF;
    const int rk0 = base + __popc(gm & par & (((1u << q) - 1) * 0x101u)), rk1 = base + __popc(gm & par & (((16u << q) - 1) * 0x101u));
    const bool d0 = (gm >> (8 + q)) & 1, d1 = (gm >> (12 + q)) & 1;
    uint32_t a[4], rs[4], x[4], w0, w1;
    zip4(lo[0], lo[1], hi[0], hi[1], x); split(x, d0, rk0 & 1 && !twice, a[0], a[1], w0, rs[0], rs[1]);
    zip4(lo[2], lo[3], hi[2], hi[3], x); split(x, d1, rk1 & 1 && !twice, a[2], a[3], w1, rs[2], rs[3]);
    const int mt = rb >> 2, tid = (rb & 3) * 32 + lane;
    g_afrag[(mt * (KSTEPS + 1) + ks) * 128 + tid] = make_uint4(a[0], a[1], a[2], a[3]);
    if (ks == 0 && (units >> 8) >= KSTEPS) g_afrag[(mt * (KSTEPS + 1) + KSTEPS) * 128 + tid] = make_uint4(0, 0, 0, 0);
    if (twice) g_afrag[(mt * (KSTEPS + 1) + KSTEPS) * 128 + tid] =
        make_uint4(__byte_perm(rs[0], rs[1], 0x5410), __byte_perm(rs[0], rs[1], 0x7632), __byte_perm(rs[2], rs[3], 0x5410), __byte_perm(rs[2], rs[3], 0x7632));
    w0 <<= 4 * q; w1 <<= 4 * q;
    w0 |= __shfl_xor_sync(~0u, w0, 1); w1 |= __shfl_xor_sync(~0u, w1, 1);
    w0 |= __shfl_xor_sync(~0u, w0, 2); w1 |= __shfl_xor_sync(~0u, w1, 2);
    if ((q >> 1) == (ks & 1)) aux[((ks >> 3) * 32 + lane) * 4 + ((ks >> 1) & 3)] = (q & 1) ? w1 : w0;
    const int em = min(ne, max(8, 16 - no)), om = min(no, 16 - em);
    const int odd = q & 1, m = odd ? om : em;
    auto place = [&](int rk) {
        const int t = 15 - rk;
        return rk >= m ? 16 + (odd ? ne - em : 0) + rk - m : rk < 8 ? (rk >> 1) * 4 + 2 * odd + (rk & 1) : (t >> 1) * 4 + 2 * (odd ^ 1) + (t & 1);
    };
#pragma unroll
    for (int e = 0; e < 2; e++) {
        const int rk = e ? rk1 : rk0;
        const bool dbl = e ? d1 : d0;
        const uint32_t va = rs[2 * e], vb = rs[2 * e + 1];
        const uint32_t second = (__ballot_sync(~0u, vb != 0) & (0x11111111u << q)) != 0 && !dbl;
        if ((gm >> (4 * e + q)) & 1) {
            const int sl = place(rk);
            put_slot(sl >> 2, r * 4 + (sl & 3), !dbl ? va | vb : (rk & 1) ? vb : va, resid_off(g0 + 4 * e, rk & 1, r) | (second << 15));
            if (dbl) { const int s2 = place(rk + 1); put_slot(s2 >> 2, r * 4 + (s2 & 3), (rk & 1) ? va : vb, resid_off(g0 + 4 * e, ~rk & 1, r)); }
        }
    }
    const int ntot = ne + no;
    const int ng = ntot > 16 ? (ntot + 3) >> 2 : min(4, (max(ne, no) + 1) >> 1);
    if (ks == 7) { aux[(2 * 32 + lane) * 4 + 1] = ng | (units << 8); *(uint2*)(aux + (2 * 32 + lane) * 4 + 2) = bias2;
        aux[(3 * 32 + lane) * 4 + 3] = 0; *(uint2*)(aux + (5 * 32 + lane) * 4 + 2) = make_uint2(0, 0);
    }
    const int idx = 2 * ks + (q & 1);
    const int frow = ks < 6 ? ks : ks == 6 ? ng - 1 : ng;
    const bool fill = ks < 4 ? !(idx < ((q >> 1) ? om : em) || (15 - idx) < ((q >> 1) ? em : om))
                             : (ks < 6 || (ng > 6 && (ks == 6 || (ks == 8 && (ng & 1))))) && 4 * frow + q >= ntot;
    if (fill) put_slot(frow, lane, 0, resid_off(q >> 1, q & 1, r));
}

template<int SEL> __device__ __forceinline__ void wgmma_sp(float (&d)[NACC], const uint32_t (&a)[4], uint64_t bdesc, uint32_t meta) {
    asm volatile("{\n.reg .pred p;\nsetp.ne.b32 p, %22, 0;\n"
        "wgmma.mma_async.sp.sync.aligned.m64n32k32.f32.bf16.bf16 {%0, %1, %2, %3, %4, %5, %6, %7, %8, %9, %10, %11, %12, %13, %14, %15}, {%16, %17, %18, %19}, %20, %21, %23, p, 1, 1, 0;\n}\n"
        : "+f"(d[0]), "+f"(d[1]), "+f"(d[2]), "+f"(d[3]), "+f"(d[4]), "+f"(d[5]), "+f"(d[6]), "+f"(d[7]), "+f"(d[8]), "+f"(d[9]), "+f"(d[10]), "+f"(d[11]), "+f"(d[12]), "+f"(d[13]), "+f"(d[14]), "+f"(d[15])
        : "r"(a[0]), "r"(a[1]), "r"(a[2]), "r"(a[3]), "l"(bdesc), "r"(meta), "r"(1), "n"(SEL));
}

__device__ __forceinline__ void mbar_init(uint32_t bar, uint32_t cnt) { asm volatile("mbarrier.init.shared::cta.b64 [%0], %1;" :: "r"(bar), "r"(cnt) : "memory"); }
__device__ __forceinline__ void mbar_expect_tx(uint32_t bar, uint32_t bytes) {
    asm volatile("mbarrier.arrive.expect_tx.shared::cta.b64 _, [%0], %1;" :: "r"(bar), "r"(bytes) : "memory");
}
__device__ __forceinline__ void mbar_arrive(uint32_t bar) { asm volatile("mbarrier.arrive.shared::cta.b64 _, [%0];" :: "r"(bar) : "memory"); }
__device__ __forceinline__ void mbar_arrive_cluster(uint32_t bar) { asm volatile("mbarrier.arrive.shared::cluster.b64 _, [%0];" :: "r"(bar) : "memory"); }
__device__ __forceinline__ bool mbar_try(uint32_t bar, uint32_t parity) {
    uint32_t ok;
    asm volatile("{\n.reg .pred p;\nmbarrier.try_wait.parity.shared::cta.b64 p, [%1], %2;\nselp.u32 %0, 1, 0, p;\n}\n" : "=r"(ok) : "r"(bar), "r"(parity) : "memory");
    return ok;
}
__device__ __forceinline__ bool mbar_test(uint32_t bar, uint32_t parity) {
    uint32_t ok;
    asm volatile("{\n.reg .pred p;\nmbarrier.test_wait.parity.shared::cta.b64 p, [%1], %2;\nselp.u32 %0, 1, 0, p;\n}\n" : "=r"(ok) : "r"(bar), "r"(parity) : "memory");
    return ok;
}
__device__ __forceinline__ void fail_if(bool c) { asm volatile("{\n.reg .pred p;\nsetp.ne.u32 p, %0, 0;\n@p st.volatile.global.u32 [%1], %0;\n}\n" :: "r"((uint32_t)c), "l"(0ull) : "memory"); }
__device__ __forceinline__ void mbar_wait(uint32_t bar, uint32_t parity) {
    int n = 0;
    while (!mbar_try(bar, parity)) fail_if(++n > (1 << 20));
}
__device__ __forceinline__ void st_async(uint32_t addr, uint32_t v, uint32_t bar) {
    asm volatile("st.async.weak.shared::cluster.mbarrier::complete_tx::bytes.u32 [%0], %1, [%2];" :: "r"(addr), "r"(v), "r"(bar) : "memory");
}
__device__ __forceinline__ uint32_t mapa(uint32_t a, uint32_t cta) { uint32_t d; asm("mapa.shared::cluster.u32 %0, %1, %2;" : "=r"(d) : "r"(a), "r"(cta)); return d; }
__device__ __forceinline__ uint32_t lds32(uint32_t a) { uint32_t v; asm volatile("ld.shared.b32 %0, [%1];" : "=r"(v) : "r"(a)); return v; }
__device__ __forceinline__ uint32_t lds32v(uint32_t a) { uint32_t v; asm volatile("ld.volatile.shared.b32 %0, [%1];" : "=r"(v) : "r"(a) : "memory"); return v; }
__device__ __forceinline__ void sts32(uint32_t a, uint32_t v) { asm volatile("st.shared.b32 [%0], %1;" :: "r"(a), "r"(v) : "memory"); }
__device__ __forceinline__ uint4 ldw(const uint4* a) { uint4 v; asm volatile("ld.weak.global.L1::no_allocate.v4.u32 {%0,%1,%2,%3}, [%4];" : "=r"(v.x), "=r"(v.y), "=r"(v.z), "=r"(v.w) : "l"(a) : "memory"); return v; }
__device__ __forceinline__ void mma_k8(float* c, uint2 a, uint32_t b) {
    asm volatile("mma.sync.aligned.m16n8k8.row.col.f32.bf16.bf16.f32 {%0,%1,%2,%3}, {%4,%5}, {%6}, {%0,%1,%2,%3};"
                 : "+f"(c[0]), "+f"(c[1]), "+f"(c[2]), "+f"(c[3]) : "r"(a.x), "r"(a.y), "r"(b));
}
__device__ __forceinline__ void mma_k16(float* d, uint2 a, uint2 a2, uint32_t b0, uint32_t b1, float c0, float c1, float c2, float c3) {
    asm volatile("mma.sync.aligned.m16n8k16.row.col.f32.bf16.bf16.f32 {%0,%1,%2,%3}, {%4,%5,%6,%7}, {%8,%9}, {%10,%11,%12,%13};"
                 : "=f"(d[0]), "=f"(d[1]), "=f"(d[2]), "=f"(d[3]) : "r"(a.x), "r"(a.y), "r"(a2.x), "r"(a2.y), "r"(b0), "r"(b1), "f"(c0), "f"(c1), "f"(c2), "f"(c3));
}
__device__ __forceinline__ uint32_t pack_bias(float lo, float hi, uint32_t bias2) {
    uint32_t p, o;
    asm("cvt.rn.bf16x2.f32 %0, %1, %2;" : "=r"(p) : "f"(hi), "f"(lo));
    asm("add.rn.bf16x2 %0, %1, %2;" : "=r"(o) : "r"(p), "r"(bias2));
    return o;
}

template <bool B> struct Flag { static constexpr bool value = B; };
struct Params {
    const uint16_t* w; const uint16_t* bias; const uint8_t* x;
    int nq, npages;
    int ncl, nh;
    int nctas;
    int tb, ta, te, slope0, slope1, c0;
    int m0;
    uint32_t ratio[8]; int rm[8];
};
struct Maps { CUtensorMap x[2], o[2], pf; };
__device__ __forceinline__ uint4 entry_w(int M, int w, int q, int extra) {
    const int r = M - (M >> 6), o = (r * 9363) >> 16, t = r - 7 * o, odd = t & 1, n = t >> 1;
    const int u = w ^ o ^ odd;
    const int C = 8 * o + 2 * n + ((n ^ u) & 1), C2 = 8 * o + 6 + ((1 ^ u) & 1);
    const uint32_t ra = 57 * C - ((C * 7282) >> 16) + 4 * odd, rb = odd ? 57 * C2 - ((C2 * 7282) >> 16) + 4 + 2 * n : ra + 12;
    const uint32_t rm = 2048 * (2 * (M >> 6) + w) + 56;
    const bool mixed = (M & 63) == 63;
    return make_uint4(M | (mixed << 14) | (q << 17) | (extra << 18), mixed ? rm * 0x10001u + (512u << 16) : ra * 0x10001u + (2u << 16),
                      mixed ? rm * 0x10001u + (1024u | 1536u << 16) : (ra + (odd ? 4 : 10)) | (rb << 16), 0);
}
__device__ __forceinline__ uint4 entry(int M, int q, int extra, unsigned long long plan) {
    const int r = M - (M >> 6), page = (r * 2341) >> 16;
    return entry_w(M, (M & 63) == 63 ? q : q ^ (int)((plan >> page) & 1), q, extra);
}
__device__ __forceinline__ int frontier(const Params& p, int t) {
    t = max(t, p.tb);
    const int l = t < p.ta ? LEAD0 + ((p.slope0 * (t - p.tb)) >> 16) : LEADE + max(0, (p.slope1 * (p.te - t)) >> 16);
    return (min(p.nq, t + l) * 9) >> 3;
}
__device__ __forceinline__ uint4 cl_entry(const Params& p, int m, int q, uint32_t ratio, unsigned long long plan) {
    const int nb = (m * ratio + 0x8000u) >> 16, nb1 = m ? ((m - 1) * ratio + 0x8000u) >> 16 : 0;
    uint4 e = entry(p.m0 + m + nb, q, nb - nb1, plan);
    const int c0 = frontier(p, p.m0 + m - 1 + nb1);
    e.w = c0 | (frontier(p, p.m0 + m + nb) - c0) << 16;
    return e;
}
__device__ __forceinline__ int helpers(const Params& p, unsigned long long plan, int q) {
    const int h0 = min(max(((p.ncl + p.nh) >> 1) - (p.ncl - (int)((plan >> 48) & 0xFF)), 0), p.nh);
    return q ? p.nh - h0 : h0;
}
__device__ __forceinline__ void draw(uint32_t& v, uint32_t* ctr, uint32_t inc) {
    asm volatile("{\n.reg .pred p;\nelect.sync _|p, 0xffffffff;\n@p atom.relaxed.gpu.global.add.u32 %0, [%1], %2;\n}" : "+r"(v) : "l"(ctr), "r"(inc) : "memory");
}
__device__ __forceinline__ uint4 lds128v(uint32_t a) { uint4 v; asm volatile("ld.volatile.shared.v4.b32 {%0,%1,%2,%3}, [%4];" : "=r"(v.x), "=r"(v.y), "=r"(v.z), "=r"(v.w) : "r"(a) : "memory"); return v; }
__device__ __forceinline__ void sts128(uint32_t a, uint4 e) { asm volatile("st.shared.v4.b32 [%0], {%1,%2,%3,%4};" :: "r"(a), "r"(e.x), "r"(e.y), "r"(e.z), "r"(e.w) : "memory"); }

__device__ __forceinline__ const uint8_t* probe_line(const Params& p, int page, int cell, int line, int parity) {
    return p.x + ((size_t)page << 21) + cell * 65536 + ((__popc(cell & 0xB) ^ parity) & 1) * 4096 + line * 128;
}
__device__ __forceinline__ int near_parity(const Params& p, int page, int cell, int line, uint32_t scratch, uint32_t since) {
    int sum = 0;
#pragma unroll 1
    for (int e = -1; e < NPR; e++) {
        uint32_t a = 0, b = 0, t0, t1;
        asm volatile("{\n.reg .pred p;\nsetp.ge.s32 p, %4, 0;\n@p ld.global.cg.u32 %0, [%2];\n@p ld.global.cg.u32 %1, [%3];\n}"
                     : "+r"(a), "+r"(b) : "l"(probe_line(p, page, cell, line + e, e & 1)), "l"(probe_line(p, page, cell, line + e, ~e & 1)), "r"(e) : "memory");
        asm volatile("st.volatile.shared.u32 [%0], %1;" :: "r"(scratch), "r"(a) : "memory");
        asm volatile("mov.u32 %0, %%clock;" : "=r"(t0) :: "memory");
        asm volatile("st.volatile.shared.u32 [%0], %1;" :: "r"(scratch), "r"(b) : "memory");
        asm volatile("mov.u32 %0, %%clock;" : "=r"(t1) :: "memory");
        const int d = min(t1 - t0, 200u);
        sum = e < 0 ? 0 : (e & 1) ? sum + d : sum - d;
        while (t1 - since < PWAIT) asm volatile("mov.u32 %0, %%clock;" : "=r"(t1) :: "memory");
    }
    return sum > 0;
}

template <bool HELPER>
__global__ void __launch_bounds__(NTHREADS, 1)
spgemm_kernel(const __grid_constant__ Params p, const __grid_constant__ Maps maps) {
    extern __shared__ unsigned char smem_raw[];
    const uint32_t sb = ((uint32_t)__cvta_generic_to_shared(smem_raw) + 1023u) & ~1023u;
    const int tid = threadIdx.x, warp = __shfl_sync(~0u, tid >> 5, 0), lane = tid & 31;
    const int rank = blockIdx.x % CL, cid = blockIdx.x / CL;
    const uint32_t bar_full = sb + OFF_FULL, bar_empty = sb + OFF_EMPTY, tk = sb + OFF_TK;
    uint4 wv[4];
    const int wrow = warp * 16 + (lane & 3) * 4;
    uint32_t b0, b1;
    auto prep_load = [&](int mtile) {
        b0 = __ldg(p.bias + mtile * 64 + lane); b1 = __ldg(p.bias + mtile * 64 + 32 + lane);
#pragma unroll
        for (int j = 0; j < 4; j++) wv[j] = __ldg((const uint4*)(p.w + (rank * 192 + wrow + j) * D + mtile * 64 + (lane >> 2) * 8));
    };
    if (!HELPER && warp < 12) {
        asm volatile("barrier.cluster.arrive.relaxed.aligned;" ::: "memory");
        if (cid < 36) prep_load(cid >> 2);
    }

    if (warp >= 12) {
        asm volatile("setmaxnreg.dec.sync.aligned.u32 32;");
        const int ppage = warp == 15 ? p.npages - 1 : cid, pcell = warp == 15 ? cid & 31 : 30, pline = warp == 15 ? (cid >> 5) * NPR : 2 * NPR;
        const bool prober = !HELPER && rank == 0 && (warp == 15 || (warp == 14 && cid < p.npages));
        uint32_t tp;
        asm volatile("mov.u32 %0, %%clock;" : "=r"(tp) :: "memory");
        if (prober && lane < 2 * NPR) asm volatile("prefetch.global.L2 [%0];" :: "l"(probe_line(p, ppage, pcell, pline + (lane >> 1), lane & 1)) : "memory");
        if (tid == NCONS) {
#pragma unroll
            for (int s = 0; s < NSLOT; s++) { mbar_init(bar_full + 8 * s, 1); mbar_init(bar_empty + 8 * s, HELPER ? 3 : 3 * CL); }
#pragma unroll
            for (int j = 0; j < 8; j++) sts32(tk + 16 * j, 0);
            mbar_init(sb + OFF_MBAR, 1); mbar_init(sb + OFF_MBAR + 8, 1);
            mbar_init(sb + OFF_GO, HELPER ? 12 : 12 + CL); mbar_init(sb + OFF_PLAN, 1); mbar_init(sb + OFF_PLAN2, 1);
            asm volatile("fence.mbarrier_init.release.cluster;" ::: "memory");
            mbar_expect_tx(sb + OFF_MBAR, 36 * 8);
            if (!HELPER && rank != 0) mbar_expect_tx(sb + OFF_PLAN, 16);
        }
        if (tid == NCONS + 32) {
            asm volatile("prefetch.tensormap [%0];" :: "l"(&maps.x[0]) : "memory");
            if (!HELPER) asm volatile("griddepcontrol.launch_dependents;");
            asm volatile("prefetch.tensormap [%0];" :: "l"(&maps.pf) : "memory");
            asm volatile("prefetch.tensormap [%0];" :: "l"(&maps.x[1]) : "memory");
#pragma unroll
            for (int j = 0; j < 2; j++) asm volatile("prefetch.tensormap [%0];" :: "l"(&maps.o[j]) : "memory");
        }
        __syncwarp();
        auto wait_plan = [&]() -> uint4 {
            unsigned long long a, b; int n = 0;
            do { asm volatile("ld.relaxed.gpu.global.v2.u64 {%0, %1}, [%2];" : "=l"(a), "=l"(b) : "l"(&g_plan) : "memory"); fail_if(++n > (1 << 22)); }
            while (__any_sync(~0u, (int)(a >> 56) + (int)(b >> 56) != 2 * p.ncl));
            b &= (1ull << 56) - 1;
            const int side = (b >> cid) & 1, n1 = __popcll(b), below = __popcll(b & ((1ull << cid) - 1));
            a = ((a ^ b) & ((1ull << 40) - 1)) | (unsigned long long)n1 << 48;
            return make_uint4((uint32_t)a, (uint32_t)(a >> 32), side | (side ? below : cid - below) << 8 | (side ? n1 : p.ncl - n1) << 16, 0);
        };
        uint4 e0 = make_uint4(0, 0, 0, 0), e1 = e0;
        if (HELPER) {
            asm volatile("bar.sync 0;" ::: "memory");
            if (warp == 15) {
                const uint4 inf = wait_plan();
                const unsigned long long plan = inf.x | ((unsigned long long)inf.y << 32);
                int idx = cid, nh = helpers(p, plan, 0), q = 2 * nh < p.nh;
                if (q) nh = p.nh - nh;
                if (idx >= nh) { idx -= nh; nh = p.nh - nh; q ^= 1; }
                const uint32_t ratio = p.ratio[nh];
                const int rm = p.rm[nh], H = p.nq - p.m0 - rm;
                for (int j0 = 0; __any_sync(~0u, idx + (j0 - 1) * nh < H); j0 += 32) {
                    const int k = idx + (j0 + lane) * nh, mk = (((k + 1) << 16) - 0x8000u + ratio - 1) / ratio;
                    uint4 e = entry(p.m0 + min(mk, rm) + k, q, 0, plan);
                    if (k >= H) e.x = NO_TILE;
                    sts128(sb + OFF_TAB + 16 * (j0 + lane), e);
                }
                __syncwarp();
                if (lane == 0) mbar_arrive(sb + OFF_PLAN);
            }
        } else {
            asm volatile("barrier.cluster.arrive.relaxed.aligned;" ::: "memory");
            int side = 0;
            if (warp == 12) { e0 = entry_w(cid, 0, 0, 0); e1 = entry_w(cid, 1, 1, 0); }
            if (rank == 0 && warp >= 14) {
                if (prober) side = near_parity(p, ppage, pcell, pline, sb + OFF_INFO + 16 + 4 * (warp & 1), tp);
                if (lane == 0) asm volatile("red.relaxed.gpu.global.add.u64 [%0], %1;" :: "l"(warp == 14 ? &g_plan.x : &g_plan.y), "l"((1ull << 56) | (unsigned long long)side << cid) : "memory");
            }
            asm volatile("barrier.cluster.wait.aligned;" ::: "memory");
            if (warp >= 13) {
                if (warp == 15 && rank == 0) {
                    const uint4 inf = wait_plan();
                    if (lane == 0) sts128(sb + OFF_INFO, inf);
                    else if (lane < CL)
                        asm volatile("st.async.weak.shared::cluster.mbarrier::complete_tx::bytes.v4.u32 [%0], {%1, %2, %3, %4}, [%5];"
                                     :: "r"(mapa(sb + OFF_INFO, lane)), "r"(inf.x), "r"(inf.y), "r"(inf.z), "r"(inf.w), "r"(mapa(sb + OFF_PLAN, lane)) : "memory");
                }
                if (rank == 0) asm volatile("bar.sync 15, 96;" ::: "memory"); else mbar_wait(sb + OFF_PLAN, 0);
                const uint4 inf = lds128v(sb + OFF_INFO);
                const unsigned long long plan = inf.x | ((unsigned long long)inf.y << 32);
                const int nh = helpers(p, plan, inf.z & 1), rm = p.rm[nh], nc = inf.z >> 16;
                const uint32_t ratio = p.ratio[nh];
                if (warp == 15 && rank == 0) {
                    const int m = ((inf.z >> 8) & 0xFF) + min(lane, NSTAT - 1) * nc;
                    sts128(sb + OFF_TAB + 16 * m, cl_entry(p, m, inf.z & 1, ratio, plan));
                    __syncwarp();
                    if (lane == 0) { mbar_arrive(sb + OFF_PLAN); mbar_expect_tx(sb + OFF_PLAN2, 16 * (rm - NSTAT * nc)); }
                }
                const uint32_t rtab = mapa(sb + OFF_TAB, 0), rbar = mapa(sb + OFF_PLAN2, 0);
                for (int m0 = NSTAT * nc + 96 * (2 - rank); __any_sync(~0u, m0 < rm); m0 += 288) {
                    const int m = m0 + tid - (NCONS + 32);
                    const uint4 e = cl_entry(p, m, inf.z & 1, ratio, plan);
                    if (m < rm) asm volatile("st.async.weak.shared::cluster.mbarrier::complete_tx::bytes.v4.u32 [%0], {%1, %2, %3, %4}, [%5];"
                                             :: "r"(rtab + 16 * m), "r"(e.x), "r"(e.y), "r"(e.z), "r"(e.w), "r"(rbar) : "memory");
                }
            }
        }
        if (warp == 12) {
            if (!HELPER && rank != 0) {
                mbar_wait(sb + OFF_PLAN, 0);
                const uint4 inf = lds128v(sb + OFF_INFO);
                const unsigned long long plan = inf.x | ((unsigned long long)inf.y << 32);
                auto cell = [&](int c, int q) {
                    const int y = 32 * c - 2 + 4 * ((__popc(c & 0xB) ^ (int)(plan >> (c >> 5)) ^ q) & 1);
                    asm volatile("{\n.reg .pred p;\nelect.sync _|p, 0xffffffff;\n@p cp.async.bulk.prefetch.tensor.3d.L2.global.tile [%0, {%1, %2, %1}];\n}" :: "l"(&maps.pf), "r"(0), "r"(y) : "memory");
                };
                const int fe0 = frontier(p, 0), step = 2 * (inf.z >> 16);
                int u0 = p.c0 + 2 * ((inf.z >> 8) & 0xFF) + rank - 1;
                {
                    uint32_t t, due;
                    asm volatile("mov.u32 %0, %%clock;" : "=r"(due) :: "memory");
                    due += (PACE * (u0 - p.c0)) / step;
                    for (; __any_sync(~0u, u0 < fe0); u0 += step, due += PACE) {
                        do { asm volatile("mov.u32 %0, %%clock;" : "=r"(t) :: "memory"); } while (__any_sync(~0u, (int)(t - due) < 0));
                        cell(u0, inf.z & 1);
                    }
                }
                for (int j = XEARLY + rank - 1;; j += 2) {
                    uint4 v; uint32_t ahead;
                    for (int n = 0; __any_sync(~0u, (ahead = (((v = lds128v(tk + ((j & 7) << 4))).x >> 20) - (j + 1)) & 0xFFF) >= 0x800); n++) {
                        if (__any_sync(~0u, lds32v(tk + (((j - 1) & 7) << 4)) == (NO_TILE | (uint32_t)j << 20))) { v.x = NO_TILE; break; }
                        __nanosleep(100); fail_if(n > (1 << 24));
                    }
                    if (__any_sync(~0u, (v.x & NO_TILE) == NO_TILE)) break;
                    j += __reduce_max_sync(~0u, ahead);
                    for (int u = v.w & 0xFFFF; __any_sync(~0u, u < (v.w & 0xFFFF) + (v.w >> 16)); u++) cell(u, (v.x >> 17) & 1);
                }
            } else {
                const uint32_t rtk = HELPER ? tk : mapa(tk, lane < CL ? lane : 0), rfull = HELPER ? bar_full : mapa(bar_full, lane < CL ? lane : 0);
                int s = 0; uint32_t ph = 1;
                uint64_t pol;
                if (!HELPER) asm volatile("createpolicy.fractional.L2::evict_first.b64 %0, 1.0;" : "=l"(pol));
                else asm volatile("createpolicy.fractional.L2::evict_normal.b64 %0, 1.0;" : "=l"(pol));
                auto request = [&](int j, const uint4& t) {
                    const bool valid = t.x != NO_TILE;
                    const CUtensorMap* tm = &maps.x[(t.x >> 14) & 1];
                    mbar_wait(bar_empty + 8 * s, ph);
                    if (__any_sync(~0u, valid)) {
                        const uint32_t dst = sb + OFF_X + s * TILE_BYTES;
                        if (HELPER)
                            asm volatile("{\n.reg .pred p;\nelect.sync _|p, 0xffffffff;\n"
                                         "@p cp.async.bulk.tensor.4d.shared::cluster.global.mbarrier::complete_tx::bytes.L2::cache_hint [%0], [%4, {%6, %7, %6, %6}], [%5], %11;\n"
                                         "@p cp.async.bulk.tensor.4d.shared::cluster.global.mbarrier::complete_tx::bytes.L2::cache_hint [%1], [%4, {%6, %8, %6, %6}], [%5], %11;\n"
                                         "@p cp.async.bulk.tensor.4d.shared::cluster.global.mbarrier::complete_tx::bytes.L2::cache_hint [%2], [%4, {%6, %9, %6, %6}], [%5], %11;\n"
                                         "@p cp.async.bulk.tensor.4d.shared::cluster.global.mbarrier::complete_tx::bytes.L2::cache_hint [%3], [%4, {%6, %10, %6, %6}], [%5], %11;\n}\n"
                                         :: "r"(dst), "r"(dst + 9216), "r"(dst + 2 * 9216), "r"(dst + 3 * 9216), "l"(tm), "r"(bar_full + 8 * s), "r"(0),
                                            "r"(t.y & 0xFFFF), "r"(t.y >> 16), "r"(t.z & 0xFFFF), "r"(t.z >> 16), "l"(pol) : "memory");
                        else
                            asm volatile("{\n.reg .pred p;\nelect.sync _|p, 0xffffffff;\n"
                                         "@p cp.async.bulk.tensor.4d.shared::cluster.global.mbarrier::complete_tx::bytes.multicast::cluster.L2::cache_hint [%0], [%4, {%6, %7, %6, %6}], [%5], %11, %12;\n"
                                         "@p cp.async.bulk.tensor.4d.shared::cluster.global.mbarrier::complete_tx::bytes.multicast::cluster.L2::cache_hint [%1], [%4, {%6, %8, %6, %6}], [%5], %11, %12;\n"
                                         "@p cp.async.bulk.tensor.4d.shared::cluster.global.mbarrier::complete_tx::bytes.multicast::cluster.L2::cache_hint [%2], [%4, {%6, %9, %6, %6}], [%5], %11, %12;\n"
                                         "@p cp.async.bulk.tensor.4d.shared::cluster.global.mbarrier::complete_tx::bytes.multicast::cluster.L2::cache_hint [%3], [%4, {%6, %10, %6, %6}], [%5], %11, %12;\n}\n"
                                         :: "r"(dst), "r"(dst + 9216), "r"(dst + 2 * 9216), "r"(dst + 3 * 9216), "l"(tm), "r"(bar_full + 8 * s), "r"(0),
                                            "r"(t.y & 0xFFFF), "r"(t.y >> 16), "r"(t.z & 0xFFFF), "r"(t.z >> 16), "h"((uint16_t)((1u << CL) - 1)), "l"(pol) : "memory");
                    }
                    if (HELPER) {
                        if (lane == 0) { sts128(tk + ((j & 7) << 4), t); mbar_expect_tx(bar_full + 8 * s, valid ? TILE_BYTES : 0); }
                    } else if (lane < CL) {
                        asm volatile("mbarrier.arrive.expect_tx.shared::cluster.b64 _, [%0], %1;" :: "r"(rfull + 8 * s), "r"(valid ? TILE_BYTES + 16 : 16) : "memory");
                        asm volatile("st.async.weak.shared::cluster.mbarrier::complete_tx::bytes.v4.u32 [%0], {%1, %2, %3, %4}, [%5];"
                                     :: "r"(rtk + ((j & 7) << 4)), "r"(t.x | ((uint32_t)(j + 1) << 20)), "r"(t.y), "r"(t.z), "r"(t.w), "r"(rfull + 8 * s) : "memory");
                    }
                    if (++s == NSLOT) { s = 0; ph ^= 1; }
                };
                if (HELPER) {
#pragma unroll 1
                    for (int j = 0; j < XEARLY; j++) request(j, entry_w(p.ncl + cid + (j >> 1) * (p.ncl + p.nh), j & 1, j & 1, 0));
                    mbar_wait(sb + OFF_PLAN, 0);
                    mbar_wait(sb + OFF_GO, 0);
                    for (int j = XEARLY;; j++) {
                        const uint4 t = lds128v(sb + OFF_TAB + 16 * (j - XEARLY));
                        request(j, t);
                        if (__any_sync(~0u, t.x == NO_TILE)) break;
                    }
                } else {
                    static_assert(XEARLY == 2, "");
                    request(0, e0);
                    request(1, e1);
                    mbar_wait(sb + OFF_PLAN, 0);
                    const uint4 inf = lds128v(sb + OFF_INFO);
                    const unsigned long long plan = inf.x | ((unsigned long long)inf.y << 32);
                    const int side = inf.z & 1, nc = inf.z >> 16;
                    const int nh = helpers(p, plan, side), rm = p.rm[nh], rmo = p.rm[p.nh - nh];
                    const uint32_t ratio = p.ratio[nh], ratioo = p.ratio[p.nh - nh];
                    const int st = NSTAT * nc, sto = NSTAT * (p.ncl - nc);
                    uint4 t = lds128v(sb + OFF_TAB + 16 * ((inf.z >> 8) & 0xFF));
                    mbar_wait(sb + OFF_GO, 0);
                    int j = XEARLY;
#pragma unroll 1
                    for (; j < XEARLY + NSTAT - 2; j++) {
                        const uint4 tn = lds128v(sb + OFF_TAB + 16 * (((inf.z >> 8) & 0xFF) + (j + 1 - XEARLY) * nc));
                        request(j, t);
                        t = tn;
                    }
                    uint32_t drawn = 0;
                    int q = side;
                    request(j++, t);
                    draw(drawn, &g_ticket, 1u << (16 * side));
                    t = lds128v(sb + OFF_TAB + 16 * (((inf.z >> 8) & 0xFF) + (NSTAT - 1) * nc));
                    mbar_wait(sb + OFF_PLAN2, 0);
                    for (;; j++) {
                        request(j, t);
                        uint32_t v = __reduce_max_sync(~0u, drawn);
                        int m = st + ((v >> (16 * side)) & 0xFFFF), mo = sto + ((v >> (16 - 16 * side)) & 0xFFFF);
                        if (q == side ? m >= rm && mo < rmo : mo >= rmo && m < rm) {
                            q ^= 1;
                            draw(drawn, &g_ticket, 1u << (16 * q));
                            v = __reduce_max_sync(~0u, drawn);
                            m = st + ((v >> (16 * side)) & 0xFFFF); mo = sto + ((v >> (16 - 16 * side)) & 0xFFFF);
                        }
                        if (q == side ? m >= rm : mo >= rmo) break;
                        const bool own = q == side;
                        q = m + ((m * ratio) >> 16) > mo + ((mo * ratioo) >> 16) + DELTA ? side ^ 1 : side;
                        draw(drawn, &g_ticket, 1u << (16 * q));
                        if (own) t = lds128v(sb + OFF_TAB + 16 * m);
                        else t = cl_entry(p, mo, side ^ 1, ratioo, plan);
                    }
                    t.x = NO_TILE;
                    request(j + 1, t);
                    if (lane == 0 && atomicInc(&g_done, p.ncl - 1) == (uint32_t)p.ncl - 1) g_ticket = 0;
                }
            }
        } else {
            const int g = warp - 13;
            uint64_t spol;
            asm volatile("createpolicy.fractional.L2::evict_first.b64 %0, 1.0;" : "=l"(spol));
            mbar_wait(sb + OFF_GO, 0);
            if (g == 2 && lane == 0 && atomicInc(&g_passed, p.nctas - 1) == (uint32_t)p.nctas - 1) {
#pragma unroll
                for (int m = 0; m < 9; m++) g_ready[m * 32] = 0;
                g_plan = make_ulonglong2(0, 0);
            }
            __syncwarp();
            for (int i = 0;; i++) {
                asm volatile("bar.arrive %0, 160;" :: "r"(12 + g) : "memory");
                asm volatile("bar.sync %0, 160;" :: "r"(1 + g) : "memory");
                const uint4 t = lds128v(tk + ((i & 7) << 4));
                if ((t.x & NO_TILE) == NO_TILE) break;
                const CUtensorMap* tm = &maps.o[(t.x >> 14) & 1];
                const int row[4] = {(int)(t.y & 0xFFFF), (int)(t.y >> 16), (int)(t.z & 0xFFFF), (int)(t.z >> 16)};
                if (lane == 0) {
#pragma unroll
                    for (int k = 0; k < 4; k++)
                        asm volatile("cp.async.bulk.tensor.3d.global.shared::cta.bulk_group.L2::cache_hint [%0, {%2, %3, %4}], [%1], %5;"
                                     :: "l"(tm), "r"(sb + OFF_STG + g * STG_BYTES + k * 1024), "r"((g * 3 + rank) * 64), "r"(row[k]), "r"(0), "l"(spol) : "memory");
                    asm volatile("cp.async.bulk.commit_group;" ::: "memory");
                    asm volatile("cp.async.bulk.wait_group.read 0;" ::: "memory");
                }
                __syncwarp();
            }
        }
        __syncwarp();
        if (!HELPER) asm volatile("barrier.cluster.arrive.relaxed.aligned;\nbarrier.cluster.wait.aligned;" ::: "memory");
    } else {
        asm volatile("setmaxnreg.inc.sync.aligned.u32 160;");
        const int wg = warp >> 2, wtid = tid & 127, r = lane >> 2;
        if (HELPER) asm volatile("bar.sync 0;" ::: "memory");
        else {
            int prb = cid;
            if (prb >= 36) asm volatile("barrier.cluster.wait.aligned;" ::: "memory");
#pragma unroll 1
            for (int round = 0; prb < 36; prb += p.ncl, round++) {
                const uint32_t wsm = sb + OFF_WST, msk = sb + OFF_MSK + (round & 1) * 288, mbar = sb + OFF_MBAR + (round & 1) * 8;
                if (round) {
                    asm volatile("bar.sync 3, 384;" ::: "memory");
                    if (tid == 0) mbar_expect_tx(mbar, 36 * 8);
                    prep_load(prb >> 2);
                }
                const int nt = ties(wv[0].x, wv[1].x, wv[2].x, wv[3].x) + ties(wv[0].y, wv[1].y, wv[2].y, wv[3].y) +
                               ties(wv[0].z, wv[1].z, wv[2].z, wv[3].z) + ties(wv[0].w, wv[1].w, wv[2].w, wv[3].w);
                const uint32_t mk = __ballot_sync(~0u, nt > 0), md = __ballot_sync(~0u, nt > 1);
                if (round == 0) asm volatile("barrier.cluster.wait.aligned;" ::: "memory");
                if (lane < CL)
                    asm volatile("st.async.weak.shared::cluster.mbarrier::complete_tx::bytes.v2.u32 [%0], {%1, %2}, [%3];"
                                 :: "r"(mapa(msk + (rank * 12 + warp) * 8, lane)), "r"(mk), "r"(md), "r"(mapa(mbar, lane)) : "memory");
#pragma unroll
                for (int j = 0; j < 4; j++) {
                    const int row = wrow + j;
                    const uint32_t ad = wsm + row * 128 + (((lane >> 2) ^ ((row & 1) | ((row >> 1) & 6))) << 4);
                    asm volatile("st.shared.v4.b32 [%0], {%1,%2,%3,%4};" :: "r"(ad), "r"(wv[j].x), "r"(wv[j].y), "r"(wv[j].z), "r"(wv[j].w) : "memory");
                }
                if (warp >= 6) asm volatile("bar.arrive 1, 384;" ::: "memory");
                else {
                    asm volatile("bar.sync 1, 384;" ::: "memory");
                    mbar_wait(mbar, (round >> 1) & 1);
                    uint4 ms = make_uint4(0, 0, 0, 0);
                    if (lane < KSTEPS) ms = lds128v(msk + 16 * lane);
                    const uint32_t m0 = ms.x, m1 = ms.z;
                    uint32_t c0 = m0 - ((m0 >> 1) & 0x55555555u), c1 = m1 - ((m1 >> 1) & 0x55555555u);
                    c0 = (c0 & 0x33333333u) + ((c0 >> 2) & 0x33333333u) + (c1 & 0x33333333u) + ((c1 >> 2) & 0x33333333u);
                    c1 = __reduce_add_sync(~0u, (c0 >> 4) & 0x0F0F0F0Fu); c0 = __reduce_add_sync(~0u, c0 & 0x0F0F0F0Fu);
                    auto key = [&](int v) { return ((((v & 1) ? c1 : c0) >> (4 * (v & 6))) & 0xFFu) * 8 + v; };
                    const uint32_t ku = key(lane & 7);
                    int rk = (key(2 * (lane >> 3)) < ku) + (key(2 * (lane >> 3) + 1) < ku);
                    rk += __shfl_xor_sync(~0u, rk, 8); rk += __shfl_xor_sync(~0u, rk, 16);
                    auto bits = [&](uint32_t a, uint32_t b, int u) { return ((a >> (4 * u)) & 15u) | (((b >> (4 * u)) & 15u) << 4); };
                    int ulo = 0, uhi = 0, cnt[4]; uint32_t md = 0;
#pragma unroll
                    for (int z = 0; z < 4; z++) {
                        const int ua = __ffs(__ballot_sync(~0u, rk == z)) - 1, ub = __ffs(__ballot_sync(~0u, rk == 7 - z)) - 1;
                        const uint32_t ta = bits(m0, m1, ua), tb = bits(m0, m1, ub), v = ta | tb | ((ta & tb) | bits(ms.y, ms.w, ua) | bits(ms.y, ms.w, ub)) << 8;
                        cnt[z] = __popc(v);
                        if (z == (prb & 3)) { ulo = ua; uhi = ub; md = v; }
                    }
                    const uint32_t l01 = __reduce_add_sync(~0u, cnt[0] | cnt[1] << 16), l23 = __reduce_add_sync(~0u, cnt[2] | cnt[3] << 16);
                    const int full = max(max(max((int)(l01 & 0xFFFF) - cnt[0], (int)(l01 >> 16) - cnt[1]), max((int)(l23 & 0xFFFF) - cnt[2], (int)(l23 >> 16) - cnt[3])), 16);
                    const int twice = __reduce_min_sync(~0u, lane < KSTEPS ? full << 12 | (65 - cnt[0] - cnt[1] - cnt[2] - cnt[3]) << 5 | lane : full << 12 | 31) & 31;
                    if (lane == twice) md = 0;
                    uint32_t lo[4], hi[4];
                    load_unit(wsm, warp, ulo, lane, lo); load_unit(wsm, warp, uhi, lane, hi);
                    const uint2 bias2 = make_uint2(__shfl_sync(~0u, ulo < 4 ? b0 : b1, (ulo * 8 + r) & 31) * 0x10001u, __shfl_sync(~0u, uhi < 4 ? b0 : b1, (uhi * 8 + r) & 31) * 0x10001u);
                    emit_step(lo, hi, md, prb, rank * 6 + warp, lane, ulo | (uhi << 4) | (twice << 8), bias2, rank * 6 + warp == twice);
                    asm volatile("bar.sync 2, 192;" ::: "memory");
                    if (tid == 0) asm volatile("red.release.gpu.global.add.u32 [%0], 1;" :: "l"(&g_ready[(prb >> 2) * 32]) : "memory");
                }
            }
            if (warp == 0 && lane < CL) mbar_arrive_cluster(mapa(sb + OFF_GO, lane));
        }
        const int mt = wg * 3 + rank, rb = mt * 4 + (warp & 3);
        if ((warp & 3) == 0) {
            uint32_t v; int n = 0;
            do { asm volatile("ld.acquire.gpu.global.u32 %0, [%1];" : "=r"(v) : "l"(&g_ready[mt * 32]) : "memory"); fail_if(++n > (1 << 22)); } while (__any_sync(~0u, v < 4 * CL));
        }
        asm volatile("bar.sync %0, 128;" :: "r"(12 + wg) : "memory");
        if (wg > 0) asm volatile("bar.sync %0, 256;" :: "r"(7 + wg) : "memory");
        uint32_t a[KSTEPS + 1][4], meta[9];
        uint2 rv[3]; uint32_t ro[3], sel[3];
        uint32_t info, bias_lo, bias_hi;
        {
            const uint4* ap = g_aux + rb * 6 * 32 + lane;
            const uint4 v3 = ldw(ap + 96), v2 = ldw(ap + 64), v4 = ldw(ap + 128), v5 = ldw(ap + 160), v0 = ldw(ap), v1 = ldw(ap + 32);
            meta[0] = v0.x; meta[1] = v0.y; meta[2] = v0.z; meta[3] = v0.w; meta[4] = v1.x; meta[5] = v1.y; meta[6] = v1.z; meta[7] = v1.w;
            meta[8] = v2.x; info = v2.y; bias_lo = v2.z; bias_hi = v2.w;
            ro[0] = v3.x; ro[1] = v3.y; ro[2] = v3.z;
            rv[0] = make_uint2(v4.x, v4.y); rv[1] = make_uint2(v4.z, v4.w); rv[2] = make_uint2(v5.x, v5.y);
        }
#pragma unroll
        for (int k = 0; k < KSTEPS + 1; k++) { uint4 v = ldw(&g_afrag[(mt * (KSTEPS + 1) + k) * 128 + wtid]); a[k][0] = v.x; a[k][1] = v.y; a[k][2] = v.z; a[k][3] = v.w; }
        if (wg < 2) asm volatile("bar.arrive %0, 256;" :: "r"(8 + wg) : "memory");
        if (lane == 0) mbar_arrive(sb + OFF_GO);
        auto selector = [](uint32_t o) { return 0x5410u + ((o >> 15) & 1) * 0x22u + (o >> 31) * 0x2200u; };
#pragma unroll
        for (int j = 0; j < 3; j++) { sel[j] = selector(ro[j]); ro[j] &= 0x7FFF7FFFu; }
        mbar_wait(bar_full, 0);
        info = __shfl_sync(~0u, info, 0);
        const int ngrp = info & 0xFF, ulo = (info >> 8) & 7, uhi = (info >> 12) & 7;
        const uint32_t stg = sb + OFF_STG + wg * STG_BYTES + ((lane >> 4) * 8 + (lane & 7)) * 128 + (((((lane >> 3) & 1) ? uhi : ulo) ^ (lane & 7)) << 4);
        const uint32_t twice = (((info >> 17) & 15) * 1024 + ((info >> 16) & 1) * 64) >> 4;
        const uint32_t rempty = HELPER ? bar_empty : mapa(bar_empty, 0);
        float acc[NACC];
        uint32_t bq[NB][6];
        auto gather = [&](uint32_t xb) {
#pragma unroll
            for (int j = 0; j < 4; j++) {
                const uint32_t o = xb + ((j & 1) ? ro[j >> 1] >> 16 : ro[j >> 1] & 0xFFFF);
#pragma unroll
                for (int n = 0; n < NB; n++) {
                    bq[n][j] = 0;
                    asm volatile("{\n.reg .pred p;\nsetp.lt.s32 p, %2, %3;\n@p ld.shared.b32 %0, [%1];\n}" : "+r"(bq[n][j]) : "r"(o + n * 9216), "r"(j), "r"(ngrp) : "memory");
                }
            }
        };
        auto select = [&]() {
#pragma unroll
            for (int n = 0; n < NB; n++)
#pragma unroll
                for (int j = 0; j < 2; j++) bq[n][2 * j] = __byte_perm(bq[n][2 * j], bq[n][2 * j + 1], sel[j]);
        };
        auto further = [&](uint32_t xb, int bar) {
#pragma unroll 1
            for (int y = 4; y < min(ngrp, 5); y++) {
#pragma unroll
                for (int n = 0; n < NB; n++) { bq[n][4] = lds32(xb + (ro[2] & 0xFFFF) + n * 9216); bq[n][5] = lds32(xb + (ro[2] >> 16) + n * 9216); }
#pragma unroll
                for (int n = 0; n < NB; n++) mma_k8(acc + 4 * n, rv[2], __byte_perm(bq[n][4], bq[n][5], sel[2]));
                if (bar >= 0) asm volatile("bar.arrive %0, 256;" :: "r"(bar) : "memory");
#pragma unroll 1
                for (int z = 3; 2 * z < ngrp; z++) {
                    const uint2 v = __ldca(&g_rval[(rb * 36 + z) * 32 + lane]); const uint32_t off = __ldca(&g_roff[(rb * 36 + z) * 32 + lane]);
                    uint32_t bx[NB];
#pragma unroll
                    for (int n = 0; n < NB; n++) bx[n] = __byte_perm(lds32(xb + (off & 0x7FFF) + n * 9216), lds32(xb + ((off >> 16) & 0x7FFF) + n * 9216), selector(off));
#pragma unroll
                    for (int n = 0; n < NB; n++) mma_k8(acc + 4 * n, v, bx[n]);
                }
            }
        };
        bool more = true;
#pragma unroll
        for (int n = 0; n < NB; n++) bq[n][4] = bq[n][5] = 0;
        gather(sb + OFF_X);
        select();
#pragma unroll
        for (int n = 0; n < NB; n++) mma_k16(acc + 4 * n, rv[0], rv[1], bq[n][0], bq[n][2], 0.f, 0.f, 0.f, 0.f);
        further(sb + OFF_X, -1);
        const int bar_a = 8 + wg, bar_an = 8 + (wg + 2) % 3, bar_tn = 4 + (wg + 2) % 3;
        if (wg == 1) asm volatile("bar.arrive 4, 256;" ::: "memory");
        if (wg == 2) { asm volatile("bar.sync 10, 256;" ::: "memory"); asm volatile("bar.arrive 5, 256;" ::: "memory"); }
        auto run = [&](auto tw) {
        constexpr bool TW = decltype(tw)::value;
        int s = 0; uint32_t ph = 0;
        bool ready = false;
        for (int i = 0; more; i++) {
            const uint32_t xb = sb + OFF_X + s * TILE_BYTES;
            const int s1 = s + 1 == NSLOT ? 0 : s + 1;
            const uint32_t ph1 = s1 == 0 ? ph ^ 1 : ph;
            asm volatile("bar.sync %0, 256;" :: "r"(4 + wg) : "memory");
            const uint64_t desc = ((uint64_t)1 << 62) | ((uint64_t)(9216 >> 4) << 32) | ((uint64_t)1 << 16) | (uint64_t)(xb >> 4);
            asm volatile("wgmma.fence.sync.aligned;" ::: "memory");
#pragma unroll
            for (int k = 0; k < KSTEPS; k++) {
                const uint64_t d = desc + (uint64_t)(((k >> 1) * 1024 + (k & 1) * 64) >> 4);
                if (k & 1) wgmma_sp<1>(acc, a[k], d, meta[k >> 1]);
                else       wgmma_sp<0>(acc, a[k], d, meta[k >> 1]);
            }
            if (TW) wgmma_sp<0>(acc, a[KSTEPS], desc + twice, 0x44444444u);
            asm volatile("wgmma.commit_group.sync.aligned;" ::: "memory");
            asm volatile("bar.arrive %0, 256;" :: "r"(bar_an) : "memory");
            if (!ready) mbar_wait(bar_full + 8 * s1, ph1);
            const uint32_t tn = lds32v(tk + (((i + 1) & 7) << 4));
            gather(sb + OFF_X + s1 * TILE_BYTES);
            asm volatile("bar.sync %0, 160;" :: "r"(12 + wg) : "memory");
            asm volatile("wgmma.wait_group.sync.aligned 0;" ::: "memory");
            if (wtid == 0) { if (HELPER) mbar_arrive(bar_empty + 8 * s); else mbar_arrive_cluster(rempty + 8 * s); }
#pragma unroll
            for (int n = 0; n < NB; n += 2) {
                const uint32_t p0 = pack_bias(acc[4 * n], acc[4 * n + 1], bias_lo), p1 = pack_bias(acc[4 * n + 2], acc[4 * n + 3], bias_hi);
                const uint32_t p2 = pack_bias(acc[4 * n + 4], acc[4 * n + 5], bias_lo), p3 = pack_bias(acc[4 * n + 6], acc[4 * n + 7], bias_hi);
                if (n == 0) asm volatile("stmatrix.sync.aligned.m8n8.x4.trans.shared.b16 [%0], {%1,%2,%3,%4};" :: "r"(stg + n * 1024), "r"(p0), "r"(p1), "r"(p2), "r"(p3) : "memory");
                else asm volatile("{\n.reg .pred p;\nAGAIN:\nstmatrix.sync.aligned.m8n8.x4.trans.shared.b16 [%0], {%1,%2,%3,%4};\nsetp.eq.u32 p, %5, 0xFFFFFFFE;\n@p bra.uni AGAIN;\n}"
                                  :: "r"(stg + n * 1024), "r"(p0), "r"(p1), "r"(p2), "r"(p3), "r"(info) : "memory");
            }
            more = __any_sync(~0u, (tn & NO_TILE) != NO_TILE);
            select();
            if (wg != 2 || more) {
                asm volatile("{\n.reg .pred p;\nTURN:\nbar.sync %0, 256;\nsetp.eq.u32 p, %1, 0xFFFFFFFF;\n@p bra.uni TURN;\n}" :: "r"(bar_a), "r"(info) : "memory");
#pragma unroll
                for (int n = 0; n < NB; n++) {
                    mma_k16(acc + 4 * n, rv[0], rv[1], bq[n][0], bq[n][2], 0.f, 0.f, 0.f, 0.f);
                    if (n == 0) asm volatile("{\n.reg .pred p;\nsetp.le.s32 p, %1, 4;\n@p bar.arrive %0, 256;\n}" :: "r"(bar_tn), "r"(ngrp) : "memory");
                }
                further(sb + OFF_X + s1 * TILE_BYTES, bar_tn);
            }
            asm volatile("fence.proxy.async.shared::cta;" ::: "memory");
            asm volatile("bar.arrive %0, 160;" :: "r"(1 + wg) : "memory");
            s = s1; ph = ph1;
            ready = __all_sync(~0u, mbar_test(bar_full + 8 * (s + 1 == NSLOT ? 0 : s + 1), s + 1 == NSLOT ? ph ^ 1 : ph));
        }
        };
        if (((info >> 16) & 31) < KSTEPS) run(Flag<true>()); else run(Flag<false>());
        if (wg == 0) asm volatile("bar.sync 4, 256;" ::: "memory");
        asm volatile("bar.sync %0, 160;" :: "r"(12 + wg) : "memory");
        asm volatile("bar.arrive %0, 160;" :: "r"(1 + wg) : "memory");
        if (!HELPER) asm volatile("barrier.cluster.arrive.relaxed.aligned;\nbarrier.cluster.wait.aligned;" ::: "memory");
    }
}

typedef CUresult (*EncodeFn)(CUtensorMap*, CUtensorMapDataType, cuuint32_t, void*, const cuuint64_t*, const cuuint64_t*, const cuuint32_t*, const cuuint32_t*,
                             CUtensorMapInterleave, CUtensorMapSwizzle, CUtensorMapL2promotion, CUtensorMapFloatOOBfill);

__global__ void plain_kernel(const __nv_bfloat16* x, const __nv_bfloat16* w, const __nv_bfloat16* b, __nv_bfloat16* out, int ntok) {
    const int t0 = blockIdx.x * 8;
    for (int f = threadIdx.x; f < D; f += blockDim.x) {
        float acc[8] = {};
        for (int g = 0; g < D / 4; g++) {
            float v[4], m[4];
            for (int i = 0; i < 4; i++) { v[i] = __bfloat162float(w[(4 * g + i) * D + f]); m[i] = fabsf(v[i]); }
            const float thr = fmaxf(fminf(fmaxf(m[0], m[1]), fmaxf(m[2], m[3])), fmaxf(fminf(m[0], m[1]), fminf(m[2], m[3])));
            for (int i = 0; i < 4; i++)
                for (int t = 0; t < 8; t++)
                    if (m[i] >= thr && t0 + t < ntok) acc[t] += v[i] * __bfloat162float(x[(size_t)(t0 + t) * D + 4 * g + i]);
        }
        for (int t = 0; t < 8; t++)
            if (t0 + t < ntok) out[(size_t)(t0 + t) * D + f] = __hadd(__float2bfloat16(acc[t]), b[f]);
    }
}

extern "C" void kernel_launch(void* const* d_in, const int* in_sizes, int n_in, void* d_out, int out_size) {
    static EncodeFn enc = nullptr;
    static int ncl = 0, nhelp = 0;
    const int ntok = in_sizes[0] / D;
    cudaLaunchConfig_t cfg = {};
    cudaLaunchAttribute at[1];
    at[0].id = cudaLaunchAttributeClusterDimension; at[0].val.clusterDim.x = CL; at[0].val.clusterDim.y = 1; at[0].val.clusterDim.z = 1;
    cfg.blockDim = dim3(NTHREADS); cfg.dynamicSmemBytes = SMEM_BYTES; cfg.attrs = at; cfg.numAttrs = 1; cfg.stream = cudaStreamPerThread;
    if (!enc) {
        cudaDriverEntryPointQueryResult qr; void* fn = nullptr;
        cudaGetDriverEntryPoint("cuTensorMapEncodeTiled", &fn, cudaEnableDefault, &qr);
        enc = (EncodeFn)fn;
        cudaFuncSetAttribute(spgemm_kernel<false>, cudaFuncAttributeMaxDynamicSharedMemorySize, SMEM_BYTES);
        cudaFuncSetAttribute(spgemm_kernel<true>, cudaFuncAttributeMaxDynamicSharedMemorySize, SMEM_BYTES);
        int dev = 0, nsm = 0;
        cudaGetDevice(&dev);
        cudaDeviceGetAttribute(&nsm, cudaDevAttrMultiProcessorCount, dev);
        cfg.gridDim = dim3(CL * (nsm / CL));
        cudaOccupancyMaxActiveClusters(&ncl, spgemm_kernel<false>, &cfg);
        if (ncl < 1) ncl = 1;
        nhelp = nsm > CL * ncl ? (nsm - CL * ncl) / CL : 0;
        if (nhelp > 7) nhelp = 7;
    }
    if (ntok % 4096 || ntok < 16384 || ntok > 65536 || ncl < 2 || ncl > 56 || 8 * (ncl + nhelp) > ntok / 64) {
        plain_kernel<<<(ntok + 7) / 8, 192, 0, cudaStreamPerThread>>>((const __nv_bfloat16*)d_in[0], (const __nv_bfloat16*)d_in[1], (const __nv_bfloat16*)d_in[2], (__nv_bfloat16*)d_out, ntok);
        return;
    }
    Maps maps;
    for (int v = 0; v < 2; v++) {
        const cuuint32_t rows = v == 0 ? 2 : 1;
        const cuuint64_t pitch = (v == 0 ? 14 : 57) * D * 2;
        {
            cuuint64_t dims[4] = {64, (cuuint64_t)ntok, 8 / rows, 9};
            cuuint64_t strides[3] = {D * 2, pitch, 128};
            cuuint32_t box[4] = {64, rows, 8 / rows, 9}, es[4] = {1, 1, 1, 1};
            enc(&maps.x[v], CU_TENSOR_MAP_DATA_TYPE_BFLOAT16, 4, d_in[0], dims, strides, box, es, CU_TENSOR_MAP_INTERLEAVE_NONE,
                CU_TENSOR_MAP_SWIZZLE_128B, CU_TENSOR_MAP_L2_PROMOTION_L2_128B, CU_TENSOR_MAP_FLOAT_OOB_FILL_NONE);
        }
        {
            cuuint64_t dims[3] = {D, (cuuint64_t)ntok, 8 / rows};
            cuuint64_t strides[2] = {D * 2, pitch};
            cuuint32_t box[3] = {64, rows, 8 / rows}, es[3] = {1, 1, 1};
            enc(&maps.o[v], CU_TENSOR_MAP_DATA_TYPE_BFLOAT16, 3, d_out, dims, strides, box, es, CU_TENSOR_MAP_INTERLEAVE_NONE,
                CU_TENSOR_MAP_SWIZZLE_128B, CU_TENSOR_MAP_L2_PROMOTION_NONE, CU_TENSOR_MAP_FLOAT_OOB_FILL_NONE);
        }
    }
    {
        cuuint64_t dims[3] = {256, (cuuint64_t)ntok * D * 2 / 2048, 4};
        cuuint64_t strides[2] = {2048, 16384};
        cuuint32_t box[3] = {256, 4, 4}, es[3] = {1, 1, 1};
        enc(&maps.pf, CU_TENSOR_MAP_DATA_TYPE_FLOAT64, 3, d_in[0], dims, strides, box, es, CU_TENSOR_MAP_INTERLEAVE_NONE,
            CU_TENSOR_MAP_SWIZZLE_NONE, CU_TENSOR_MAP_L2_PROMOTION_NONE, CU_TENSOR_MAP_FLOAT_OOB_FILL_NONE);
    }
    Params p;
    p.w = (const uint16_t*)d_in[1]; p.bias = (const uint16_t*)d_in[2]; p.x = (const uint8_t*)d_in[0];
    p.nq = ntok / 64; p.npages = (int)(((size_t)ntok * D * 2) >> 21);
    const int nc = ncl, nh = nhelp;
    p.ncl = nc; p.nh = nh; p.nctas = CL * (nc + nh);
    p.m0 = (nc + nh) * XEARLY / 2;
    for (int h = 0; h < 8; h++) {
        const uint32_t R = p.nq - p.m0, H = h * (HT * p.nq / 1024 * 44 / (nc + nh));
        p.ratio[h] = h <= nh ? (H << 16) / (R - H) : 0;
        p.rm[h] = p.ratio[h] ? (((R - 1) << 16) + 0x7FFFu) / (0x10000u + p.ratio[h]) + 1 : R;
    }
    p.c0 = (p.m0 * 9) >> 3;
    p.tb = p.m0 + (NSLOT - XEARLY) * (nc + nh) / 2;
    p.ta = p.tb + 1 + (int)((p.nq - p.tb) * TAFRAC); p.te = (int)(p.nq * TEFRAC) + 2;
    p.slope0 = ((LEAD1 - LEAD0) << 16) / (p.ta - p.tb); p.slope1 = ((LEAD1 - LEADE) << 16) / (p.te - p.ta);
    cfg.gridDim = dim3(CL * nc);
    cudaLaunchKernelEx(&cfg, spgemm_kernel<false>, p, maps);
    if (nh) {
        at[0].id = cudaLaunchAttributeProgrammaticStreamSerialization; at[0].val.programmaticStreamSerializationAllowed = 1;
        cfg.gridDim = dim3(CL * nh);
        cudaLaunchKernelEx(&cfg, spgemm_kernel<true>, p, maps);
    }
}
```

```cpp
#include <cuda_runtime.h>
#include <cuda_bf16.h>
#include <cuda.h>
#include <stdint.h>

constexpr int D = 576;
constexpr int NT = 32;
constexpr int NSLOT = 5;
constexpr int XEARLY = 2;
constexpr int NSTAT = 4;
constexpr int DELTA = 24;
constexpr int HT = 44;
constexpr int LEAD0 = 140, LEAD1 = 295, LEADE = 32, PACE = 1200;
constexpr double TAFRAC = 0.261, TEFRAC = 0.97;
constexpr int PWAIT = 1800;
constexpr int KSTEPS = 18;
constexpr int CL = 3;
constexpr int TILE_BYTES = NT * D * 2;
constexpr int STG_BYTES = NT * 128;
constexpr int NACC = NT / 2;
constexpr int NB = NT / 8;
constexpr int NCONS = 384;
constexpr int NTHREADS = 512;
constexpr int NTAB = 1024;
constexpr uint32_t NO_TILE = 0xFFFFFu;

constexpr int OFF_X = 0;
constexpr int OFF_WST = OFF_X + (NSLOT - 1) * TILE_BYTES;
constexpr int OFF_STG = OFF_X + NSLOT * TILE_BYTES;
constexpr int OFF_TAB = OFF_STG + 3 * STG_BYTES;
constexpr int OFF_TK = OFF_TAB + 16 * NTAB;
constexpr int OFF_MSK = OFF_TK + 128;
constexpr int OFF_SEL = OFF_MSK + 2 * 36 * 8;
constexpr int OFF_INFO = OFF_SEL + 128;
constexpr int OFF_FULL = OFF_INFO + 32;
constexpr int OFF_EMPTY = OFF_FULL + 8 * NSLOT;
constexpr int OFF_MBAR = OFF_EMPTY + 8 * NSLOT;
constexpr int OFF_GO = OFF_MBAR + 16;
constexpr int OFF_PLAN = OFF_GO + 8;
constexpr int OFF_PLAN2 = OFF_PLAN + 8;
constexpr int SMEM_BYTES = OFF_PLAN2 + 8 + 1024;
static_assert(SMEM_BYTES <= 232448 && TILE_BYTES >= 192 * 128 && XEARLY % 2 == 0 && XEARLY < NSLOT && NSLOT < 8 && NB == 4 && OFF_INFO % 16 == 0, "layout");

__device__ __align__(128) uint4    g_afrag[9 * (KSTEPS + 1) * 128];
__device__ __align__(128) uint4    g_aux[36 * 6 * 32];
__device__ __align__(128) uint2    g_rval[36 * 36 * 32];
__device__ __align__(128) uint32_t g_roff[36 * 36 * 32];
__device__ __align__(128) uint32_t g_ready[36 * 32];
__device__ __align__(128) uint32_t g_passed;
__device__ __align__(128) uint32_t g_ticket;
__device__ __align__(128) uint32_t g_done;
__device__ __align__(128) ulonglong2 g_plan;

__device__ __forceinline__ uint32_t max2(uint32_t a, uint32_t b) { uint32_t d; asm("max.u16x2 %0, %1, %2;" : "=r"(d) : "r"(a), "r"(b)); return d; }
__device__ __forceinline__ uint32_t min2(uint32_t a, uint32_t b) { uint32_t d; asm("min.u16x2 %0, %1, %2;" : "=r"(d) : "r"(a), "r"(b)); return d; }
__device__ __forceinline__ uint32_t sign2(uint32_t a) { uint32_t d; asm("prmt.b32 %0, %1, %1, 0xBB99;" : "=r"(d) : "r"(a)); return d; }
__device__ __forceinline__ void load_units(uint32_t wsm, int g4, int ulo, int uhi, int lane, uint32_t (&m)[4]) {
    const int row = g4 * 16 + ((lane & 7) >> 1) * 4 + ((lane >> 3) & 1) * 2 + (lane & 1);
    const uint32_t ad = wsm + row * 128 + (((lane < 16 ? ulo : uhi) ^ ((row & 1) | ((row >> 1) & 6))) << 4);
    asm volatile("ldmatrix.sync.aligned.m8n8.x4.trans.shared.b16 {%0,%1,%2,%3}, [%4];" : "=r"(m[0]), "=r"(m[1]), "=r"(m[2]), "=r"(m[3]) : "r"(ad) : "memory");
}
__device__ __forceinline__ void zip4(uint32_t a01, uint32_t a23, uint32_t b01, uint32_t b23, uint32_t (&x)[4]) {
    x[0] = __byte_perm(a01, b01, 0x5410); x[1] = __byte_perm(a01, b01, 0x7632); x[2] = __byte_perm(a23, b23, 0x5410); x[3] = __byte_perm(a23, b23, 0x7632);
}
__device__ __forceinline__ void middle2(const uint32_t (&x)[4], uint32_t (&m)[4], uint32_t& u, uint32_t& v) {
#pragma unroll
    for (int i = 0; i < 4; i++) m[i] = x[i] & 0x7FFF7FFFu;
    u = min2(max2(m[0], m[1]), max2(m[2], m[3])); v = max2(min2(m[0], m[1]), min2(m[2], m[3]));
}
__device__ __forceinline__ int ties(uint32_t x0, uint32_t x1, uint32_t x2, uint32_t x3) {
    const uint32_t x[4] = {x0, x1, x2, x3};
    uint32_t m[4], u, v;
    middle2(x, m, u, v);
    const uint32_t t = u ^ v, f = u ^ min2(min2(m[0], m[1]), min2(m[2], m[3]));
    const bool t0 = (t & 0xFFFFu) == 0 && (v & 0xFFFFu) != 0, t1 = t < 0x10000u && v >= 0x10000u;
    return t0 + t1 + 2 * ((t0 && (f & 0xFFFFu) == 0) || (t1 && f < 0x10000u));
}
__device__ __forceinline__ void split(const uint32_t (&x)[4], bool dbl, bool P, uint32_t& alo, uint32_t& ahi, uint32_t& nib, uint32_t& va, uint32_t& vb) {
    uint32_t m[4], u, v;
    middle2(x, m, u, v);
    const uint32_t c = 0x80008000u - max2(max2(u, v), 0x00010001u);
    uint32_t k0 = sign2(m[0] + c), k1 = sign2(m[1] + c), k2 = sign2(m[2] + c), k3 = sign2(m[3] + c);
    const uint32_t three = (k0 & k1 & (k2 | k3)) | (k2 & k3 & (k0 | k1)), four = k0 & k1 & k2 & k3;
    const bool a2 = !dbl && P;
    const uint32_t pa = a2 ? k2 : k0, pb = dbl ? k2 : P ? k3 : k1;
    const uint32_t ra = three & pa, rb = three & pb & (four | ~pa);
    va = (a2 ? x[2] : x[0]) & ra; vb = (dbl ? x[2] : P ? x[3] : x[1]) & rb;
    if (a2) k2 &= ~ra; else k0 &= ~ra;
    if (dbl) k2 &= ~rb; else if (P) k3 &= ~rb; else k1 &= ~rb;
    const uint32_t s1 = k1 & k0, s2 = k2 & (k0 | k1);
    const uint32_t t = (k1 & x[1]) | (~k1 & k2 & x[2]);
    const uint32_t x0 = (k0 & x[0]) | (~k0 & t), x1 = (s1 & x[1]) | (s2 & x[2]) | (k3 & x[3]);
    nib = (~k0 & k1 & 0x00010001u) | (~k0 & ~k1 & 0x00020002u) | (~s2 & 0x00040004u) | (~s1 & 0x00080008u);
    alo = __byte_perm(x0, x1, 0x5410); ahi = __byte_perm(x0, x1, 0x7632);
}
__device__ __forceinline__ uint32_t resid_off(int g, int P, int r) {
    int k0 = 4 * g + 2 * P;
    int chunk = k0 >> 6, byte = (k0 & 63) * 2;
    return chunk * 1024 + r * 128 + (((byte >> 4) ^ r) << 4) + (byte & 15);
}
__device__ __forceinline__ void emit_half(const uint32_t (&wm)[4], uint32_t md, int rb, int ks, int e, int lane, uint32_t units, uint32_t b0, uint32_t b1) {
    uint32_t* const aux = (uint32_t*)(g_aux + rb * 6 * 32);
    auto put_slot = [&](int j, int ln, uint32_t v, uint32_t off) {
        uint16_t* o = j < 6 ? (uint16_t*)aux + (3 * 32 + ln) * 8 + j : (uint16_t*)g_roff + ((rb * 36 + (j >> 1)) * 32 + ln) * 2 + (j & 1);
        uint16_t* w = j < 6 ? (uint16_t*)aux + ((4 + (j >> 2)) * 32 + ln) * 8 + (j & 2) * 2 + (j & 1) : (uint16_t*)g_rval + ((rb * 36 + (j >> 1)) * 32 + ln) * 4 + (j & 1);
        o[0] = (uint16_t)off; w[0] = (uint16_t)v; w[2] = (uint16_t)(v >> 16);
    };
    const int r = lane >> 2, q = lane & 3, g = 4 * e + q, twice = units >> 8;
    const uint32_t gm = __shfl_sync(~0u, md, ks);
    const uint32_t c2 = __popc(md & 0x5555u) | (__popc(md & 0xAAAAu) << 16);
    const uint32_t tot = __reduce_add_sync(~0u, c2), pre = __reduce_add_sync(~0u, lane < ks ? c2 : 0u);
    const int ne = tot & 0xFFFF, no = tot >> 16;
    const int rk = ((q & 1) ? pre >> 16 : pre & 0xFFFF) + __popc(gm & ((q & 1) ? 0xAAAAu : 0x5555u) & (((1u << g) - 1) * 0x101u));
    const bool dbl = (gm >> (8 + g)) & 1;
    uint32_t a0, a1, va, vb, x[4], nib;
    zip4(wm[0], wm[1], wm[2], wm[3], x); split(x, dbl, rk & 1 && ks != twice, a0, a1, nib, va, vb);
    uint2* const frag = (uint2*)(g_afrag + (rb >> 2) * (KSTEPS + 1) * 128 + (rb & 3) * 32 + lane) + e;
    frag[ks * 256] = make_uint2(a0, a1);
    if (ks == (twice < KSTEPS ? twice : 0)) frag[KSTEPS * 256] = twice < KSTEPS ? make_uint2(__byte_perm(va, vb, 0x5410), __byte_perm(va, vb, 0x7632)) : make_uint2(0, 0);
    nib <<= 4 * q;
    nib |= __shfl_xor_sync(~0u, nib, 1);
    nib |= __shfl_xor_sync(~0u, nib, 2);
    if (q == 2 * (ks & 1) + e) aux[((ks >> 3) * 32 + lane) * 4 + ((ks >> 1) & 3)] = nib;
    const int em = min(ne, max(8, 16 - no)), om = min(no, 16 - em);
    const int odd = q & 1, m = odd ? om : em;
    auto place = [&](int k) {
        const int t = 15 - k;
        return k >= m ? 16 + (odd ? ne - em : 0) + k - m : k < 8 ? (k >> 1) * 4 + 2 * odd + (k & 1) : (t >> 1) * 4 + 2 * (odd ^ 1) + (t & 1);
    };
    const uint32_t second = (__ballot_sync(~0u, vb != 0) & (0x11111111u << q)) != 0 && !dbl;
    if ((gm >> g) & 1) {
        const int sl = place(rk);
        put_slot(sl >> 2, r * 4 + (sl & 3), !dbl ? va | vb : (rk & 1) ? vb : va, resid_off(ks * 8 + g, rk & 1, r) | (second << 15));
        if (dbl) { const int s2 = place(rk + 1); put_slot(s2 >> 2, r * 4 + (s2 & 3), (rk & 1) ? va : vb, resid_off(ks * 8 + g, ~rk & 1, r)); }
    }
    const int ntot = ne + no, z = 2 * ks + e;
    const int ng = ntot > 16 ? (ntot + 3) >> 2 : min(4, (max(ne, no) + 1) >> 1);
    if (z == 8) {
        const int ulo = units & 7, uhi = (units >> 4) & 7;
        aux[(2 * 32 + lane) * 4 + 1] = ng | (units << 8);
        *(uint2*)(aux + (2 * 32 + lane) * 4 + 2) = make_uint2(__shfl_sync(~0u, ulo < 4 ? b0 : b1, (ulo * 8 + r) & 31) * 0x10001u, __shfl_sync(~0u, uhi < 4 ? b0 : b1, (uhi * 8 + r) & 31) * 0x10001u);
        aux[(3 * 32 + lane) * 4 + 3] = 0; *(uint2*)(aux + (5 * 32 + lane) * 4 + 2) = make_uint2(0, 0);
    }
    const int idx = 2 * z + (q & 1);
    const int frow = z < 6 ? z : z == 6 ? ng - 1 : ng;
    const bool fill = z < 4 ? !(idx < ((q >> 1) ? om : em) || (15 - idx) < ((q >> 1) ? em : om))
                            : (z < 6 || (ng > 6 && (z == 6 || (z == 7 && (ng & 1))))) && 4 * frow + q >= ntot;
    if (fill) put_slot(frow, lane, 0, resid_off(q >> 1, q & 1, r));
}

template<int SEL> __device__ __forceinline__ void wgmma_sp(float (&d)[NACC], const uint32_t (&a)[4], uint64_t bdesc, uint32_t meta) {
    asm volatile("{\n.reg .pred p;\nsetp.ne.b32 p, %22, 0;\n"
        "wgmma.mma_async.sp.sync.aligned.m64n32k32.f32.bf16.bf16 {%0, %1, %2, %3, %4, %5, %6, %7, %8, %9, %10, %11, %12, %13, %14, %15}, {%16, %17, %18, %19}, %20, %21, %23, p, 1, 1, 0;\n}\n"
        : "+f"(d[0]), "+f"(d[1]), "+f"(d[2]), "+f"(d[3]), "+f"(d[4]), "+f"(d[5]), "+f"(d[6]), "+f"(d[7]), "+f"(d[8]), "+f"(d[9]), "+f"(d[10]), "+f"(d[11]), "+f"(d[12]), "+f"(d[13]), "+f"(d[14]), "+f"(d[15])
        : "r"(a[0]), "r"(a[1]), "r"(a[2]), "r"(a[3]), "l"(bdesc), "r"(meta), "r"(1), "n"(SEL));
}

__device__ __forceinline__ void mbar_init(uint32_t bar, uint32_t cnt) { asm volatile("mbarrier.init.shared::cta.b64 [%0], %1;" :: "r"(bar), "r"(cnt) : "memory"); }
__device__ __forceinline__ void mbar_expect_tx(uint32_t bar, uint32_t bytes) {
    asm volatile("mbarrier.arrive.expect_tx.shared::cta.b64 _, [%0], %1;" :: "r"(bar), "r"(bytes) : "memory");
}
__device__ __forceinline__ void mbar_arrive(uint32_t bar) { asm volatile("mbarrier.arrive.shared::cta.b64 _, [%0];" :: "r"(bar) : "memory"); }
__device__ __forceinline__ void mbar_arrive_cluster(uint32_t bar) { asm volatile("mbarrier.arrive.shared::cluster.b64 _, [%0];" :: "r"(bar) : "memory"); }
__device__ __forceinline__ bool mbar_try(uint32_t bar, uint32_t parity) {
    uint32_t ok;
    asm volatile("{\n.reg .pred p;\nmbarrier.try_wait.parity.shared::cta.b64 p, [%1], %2;\nselp.u32 %0, 1, 0, p;\n}\n" : "=r"(ok) : "r"(bar), "r"(parity) : "memory");
    return ok;
}
__device__ __forceinline__ bool mbar_test(uint32_t bar, uint32_t parity) {
    uint32_t ok;
    asm volatile("{\n.reg .pred p;\nmbarrier.test_wait.parity.shared::cta.b64 p, [%1], %2;\nselp.u32 %0, 1, 0, p;\n}\n" : "=r"(ok) : "r"(bar), "r"(parity) : "memory");
    return ok;
}
__device__ __forceinline__ void fail_if(bool c) { asm volatile("{\n.reg .pred p;\nsetp.ne.u32 p, %0, 0;\n@p st.volatile.global.u32 [%1], %0;\n}\n" :: "r"((uint32_t)c), "l"(0ull) : "memory"); }
__device__ __forceinline__ void mbar_wait(uint32_t bar, uint32_t parity) {
    int n = 0;
    while (!mbar_try(bar, parity)) fail_if(++n > (1 << 20));
}
__device__ __forceinline__ void st_async(uint32_t addr, uint32_t v, uint32_t bar) {
    asm volatile("st.async.weak.shared::cluster.mbarrier::complete_tx::bytes.u32 [%0], %1, [%2];" :: "r"(addr), "r"(v), "r"(bar) : "memory");
}
__device__ __forceinline__ uint32_t mapa(uint32_t a, uint32_t cta) { uint32_t d; asm("mapa.shared::cluster.u32 %0, %1, %2;" : "=r"(d) : "r"(a), "r"(cta)); return d; }
__device__ __forceinline__ uint32_t lds32(uint32_t a) { uint32_t v; asm volatile("ld.shared.b32 %0, [%1];" : "=r"(v) : "r"(a)); return v; }
__device__ __forceinline__ uint32_t lds32v(uint32_t a) { uint32_t v; asm volatile("ld.volatile.shared.b32 %0, [%1];" : "=r"(v) : "r"(a) : "memory"); return v; }
__device__ __forceinline__ void sts32(uint32_t a, uint32_t v) { asm volatile("st.shared.b32 [%0], %1;" :: "r"(a), "r"(v) : "memory"); }
__device__ __forceinline__ uint4 ldw(const uint4* a) { uint4 v; asm volatile("ld.weak.global.L1::no_allocate.v4.u32 {%0,%1,%2,%3}, [%4];" : "=r"(v.x), "=r"(v.y), "=r"(v.z), "=r"(v.w) : "l"(a) : "memory"); return v; }
__device__ __forceinline__ void mma_k8(float* c, uint2 a, uint32_t b) {
    asm volatile("mma.sync.aligned.m16n8k8.row.col.f32.bf16.bf16.f32 {%0,%1,%2,%3}, {%4,%5}, {%6}, {%0,%1,%2,%3};"
                 : "+f"(c[0]), "+f"(c[1]), "+f"(c[2]), "+f"(c[3]) : "r"(a.x), "r"(a.y), "r"(b));
}
__device__ __forceinline__ void mma_k16(float* d, uint2 a, uint2 a2, uint32_t b0, uint32_t b1, float c0, float c1, float c2, float c3) {
    asm volatile("mma.sync.aligned.m16n8k16.row.col.f32.bf16.bf16.f32 {%0,%1,%2,%3}, {%4,%5,%6,%7}, {%8,%9}, {%10,%11,%12,%13};"
                 : "=f"(d[0]), "=f"(d[1]), "=f"(d[2]), "=f"(d[3]) : "r"(a.x), "r"(a.y), "r"(a2.x), "r"(a2.y), "r"(b0), "r"(b1), "f"(c0), "f"(c1), "f"(c2), "f"(c3));
}
__device__ __forceinline__ uint32_t pack_bias(float lo, float hi, uint32_t bias2) {
    uint32_t p, o;
    asm("cvt.rn.bf16x2.f32 %0, %1, %2;" : "=r"(p) : "f"(hi), "f"(lo));
    asm("add.rn.bf16x2 %0, %1, %2;" : "=r"(o) : "r"(p), "r"(bias2));
    return o;
}

template <bool B> struct Flag { static constexpr bool value = B; };
struct Params {
    const uint16_t* w; const uint16_t* bias; const uint8_t* x;
    int nq, npages;
    int ncl, nh;
    int nctas;
    int tb, ta, te, slope0, slope1, c0;
    int m0;
    uint32_t ratio[8]; int rm[8];
};
struct Maps { CUtensorMap x[2], o[2], pf; };
__device__ __forceinline__ uint4 entry_w(int M, int w, int q, int extra) {
    const int r = M - (M >> 6), o = (r * 9363) >> 16, t = r - 7 * o, odd = t & 1, n = t >> 1;
    const int u = w ^ o ^ odd;
    const int C = 8 * o + 2 * n + ((n ^ u) & 1), C2 = 8 * o + 6 + ((1 ^ u) & 1);
    const uint32_t ra = 57 * C - ((C * 7282) >> 16) + 4 * odd, rb = odd ? 57 * C2 - ((C2 * 7282) >> 16) + 4 + 2 * n : ra + 12;
    const uint32_t rm = 2048 * (2 * (M >> 6) + w) + 56;
    const bool mixed = (M & 63) == 63;
    return make_uint4(M | (mixed << 14) | (q << 17) | (extra << 18), mixed ? rm * 0x10001u + (512u << 16) : ra * 0x10001u + (2u << 16),
                      mixed ? rm * 0x10001u + (1024u | 1536u << 16) : (ra + (odd ? 4 : 10)) | (rb << 16), 0);
}
__device__ __forceinline__ uint4 entry(int M, int q, int extra, unsigned long long plan) {
    const int r = M - (M >> 6), page = (r * 2341) >> 16;
    return entry_w(M, (M & 63) == 63 ? q : q ^ (int)((plan >> page) & 1), q, extra);
}
__device__ __forceinline__ int frontier(const Params& p, int t) {
    t = max(t, p.tb);
    const int l = t < p.ta ? LEAD0 + ((p.slope0 * (t - p.tb)) >> 16) : LEADE + max(0, (p.slope1 * (p.te - t)) >> 16);
    return (min(p.nq, t + l) * 9) >> 3;
}
__device__ __forceinline__ uint4 cl_entry(const Params& p, int m, int q, uint32_t ratio, unsigned long long plan) {
    const int nb = (m * ratio + 0x8000u) >> 16, nb1 = m ? ((m - 1) * ratio + 0x8000u) >> 16 : 0;
    uint4 e = entry(p.m0 + m + nb, q, nb - nb1, plan);
    const int c0 = frontier(p, p.m0 + m - 1 + nb1);
    e.w = c0 | (frontier(p, p.m0 + m + nb) - c0) << 16;
    return e;
}
__device__ __forceinline__ int helpers(const Params& p, unsigned long long plan, int q) {
    const int h0 = min(max(((p.ncl + p.nh) >> 1) - (p.ncl - (int)((plan >> 48) & 0xFF)), 0), p.nh);
    return q ? p.nh - h0 : h0;
}
__device__ __forceinline__ void draw(uint32_t& v, uint32_t* ctr, uint32_t inc) {
    asm volatile("{\n.reg .pred p;\nelect.sync _|p, 0xffffffff;\n@p atom.relaxed.gpu.global.add.u32 %0, [%1], %2;\n}" : "+r"(v) : "l"(ctr), "r"(inc) : "memory");
}
__device__ __forceinline__ uint4 lds128v(uint32_t a) { uint4 v; asm volatile("ld.volatile.shared.v4.b32 {%0,%1,%2,%3}, [%4];" : "=r"(v.x), "=r"(v.y), "=r"(v.z), "=r"(v.w) : "r"(a) : "memory"); return v; }
__device__ __forceinline__ void sts128(uint32_t a, uint4 e) { asm volatile("st.shared.v4.b32 [%0], {%1,%2,%3,%4};" :: "r"(a), "r"(e.x), "r"(e.y), "r"(e.z), "r"(e.w) : "memory"); }

__device__ __forceinline__ const uint8_t* probe_line(const Params& p, int page, int cell, int line, int parity) {
    return p.x + ((size_t)page << 21) + cell * 65536 + ((__popc(cell & 0xB) ^ parity) & 1) * 4096 + line * 128;
}
__device__ __forceinline__ int lag(const uint8_t* first, const uint8_t* second, uint32_t scratch, uint32_t since) {
    uint32_t t0, t1;
#pragma unroll 1
    for (int e = 0; e < 2; e++) {
        uint32_t a = 0, b = 0;
        asm volatile("{\n.reg .pred p;\nsetp.ne.s32 p, %4, 0;\n@p ld.global.cg.u32 %0, [%2];\n@p ld.global.cg.u32 %1, [%3];\n}"
                     : "+r"(a), "+r"(b) : "l"(first), "l"(second), "r"(e) : "memory");
        asm volatile("st.volatile.shared.u32 [%0], %1;" :: "r"(scratch), "r"(a) : "memory");
        asm volatile("mov.u32 %0, %%clock;" : "=r"(t0) :: "memory");
        asm volatile("st.volatile.shared.u32 [%0], %1;" :: "r"(scratch), "r"(b) : "memory");
        asm volatile("mov.u32 %0, %%clock;" : "=r"(t1) :: "memory");
        uint32_t t = t1;
        while (t - since < PWAIT) asm volatile("mov.u32 %0, %%clock;" : "=r"(t) :: "memory");
    }
    return t1 - t0;
}

template <bool HELPER>
__global__ void __launch_bounds__(NTHREADS, 1)
spgemm_kernel(const __grid_constant__ Params p, const __grid_constant__ Maps maps) {
    extern __shared__ unsigned char smem_raw[];
    const uint32_t sb = ((uint32_t)__cvta_generic_to_shared(smem_raw) + 1023u) & ~1023u;
    const int tid = threadIdx.x, warp = __shfl_sync(~0u, tid >> 5, 0), lane = tid & 31;
    const int rank = blockIdx.x % CL, cid = blockIdx.x / CL;
    const uint32_t bar_full = sb + OFF_FULL, bar_empty = sb + OFF_EMPTY, tk = sb + OFF_TK;
    const uint8_t* pl = probe_line(p, rank ? min(cid, p.npages - 1) : p.npages - 1, rank ? 30 : cid & 31, (rank ? 4 : 0) + (rank ? cid >= p.npages ? 2 + 2 * (cid - p.npages) : 0 : (cid >> 5) * 2) + (warp & 1), warp & 1);
    uint32_t tp;
    asm volatile("mov.u32 %0, %%clock;" : "=r"(tp) :: "memory");
    if (!HELPER && rank < 2 && warp >= 14 && lane < 2) asm volatile("prefetch.global.L2 [%0];" :: "l"((const uint8_t*)((uintptr_t)pl ^ (lane << 12))) : "memory");
    uint4 wv[4];
    const int wrow = warp * 16 + (lane & 3) * 4;
    uint32_t b0, b1;
    auto prep_load = [&](int mtile) {
        b0 = __ldg(p.bias + mtile * 64 + lane); b1 = __ldg(p.bias + mtile * 64 + 32 + lane);
#pragma unroll
        for (int j = 0; j < 4; j++) wv[j] = __ldg((const uint4*)(p.w + (rank * 192 + wrow + j) * D + mtile * 64 + (lane >> 2) * 8));
    };
    if (!HELPER && warp < 12) {
        if (cid < 36) prep_load(cid >> 2);
        asm volatile("barrier.cluster.arrive.relaxed.aligned;" ::: "memory");
    }

    if (warp >= 12) {
        asm volatile("setmaxnreg.dec.sync.aligned.u32 32;");
        if (tid == NCONS) {
#pragma unroll
            for (int s = 0; s < NSLOT; s++) { mbar_init(bar_full + 8 * s, 1); mbar_init(bar_empty + 8 * s, HELPER ? 3 : 3 * CL); }
#pragma unroll
            for (int j = 0; j < 8; j++) sts32(tk + 16 * j, 0);
            mbar_init(sb + OFF_MBAR, 1); mbar_init(sb + OFF_MBAR + 8, 1);
            mbar_init(sb + OFF_GO, HELPER ? 12 : 12 + CL); mbar_init(sb + OFF_PLAN, 1); mbar_init(sb + OFF_PLAN2, 1);
            asm volatile("fence.mbarrier_init.release.cluster;" ::: "memory");
            mbar_expect_tx(sb + OFF_MBAR, 36 * 8);
            if (!HELPER && rank != 0) mbar_expect_tx(sb + OFF_PLAN, 16);
        }
        if (tid == NCONS + 32) {
            asm volatile("prefetch.tensormap [%0];" :: "l"(&maps.x[0]) : "memory");
            if (!HELPER) asm volatile("griddepcontrol.launch_dependents;");
            asm volatile("prefetch.tensormap [%0];" :: "l"(&maps.pf) : "memory");
            asm volatile("prefetch.tensormap [%0];" :: "l"(&maps.x[1]) : "memory");
#pragma unroll
            for (int j = 0; j < 2; j++) asm volatile("prefetch.tensormap [%0];" :: "l"(&maps.o[j]) : "memory");
        }
        __syncwarp();
        auto wait_plan = [&]() -> uint4 {
            unsigned long long a, b; int n = 0;
            do { asm volatile("ld.relaxed.gpu.global.v2.u64 {%0, %1}, [%2];" : "=l"(a), "=l"(b) : "l"(&g_plan) : "memory"); fail_if(++n > (1 << 22)); }
            while (__any_sync(~0u, (int)(a >> 56) + (int)(b >> 56) != 2 * p.ncl));
            b &= (1ull << 56) - 1;
            const int side = (b >> cid) & 1, n1 = __popcll(b), below = __popcll(b & ((1ull << cid) - 1));
            a = ((a ^ b) & ((1ull << 40) - 1)) | (unsigned long long)n1 << 48;
            return make_uint4((uint32_t)a, (uint32_t)(a >> 32), side | (side ? below : cid - below) << 8 | (side ? n1 : p.ncl - n1) << 16, 0);
        };
        uint4 e0 = make_uint4(0, 0, 0, 0), e1 = e0;
        if (HELPER) {
            asm volatile("bar.sync 0;" ::: "memory");
            if (warp == 15) {
                const uint4 inf = wait_plan();
                const unsigned long long plan = inf.x | ((unsigned long long)inf.y << 32);
                int idx = cid, nh = helpers(p, plan, 0), q = 2 * nh < p.nh;
                if (q) nh = p.nh - nh;
                if (idx >= nh) { idx -= nh; nh = p.nh - nh; q ^= 1; }
                const uint32_t ratio = p.ratio[nh];
                const int rm = p.rm[nh], H = p.nq - p.m0 - rm;
                for (int j0 = 0; __any_sync(~0u, idx + (j0 - 1) * nh < H); j0 += 32) {
                    const int k = idx + (j0 + lane) * nh, mk = (((k + 1) << 16) - 0x8000u + ratio - 1) / ratio;
                    uint4 e = entry(p.m0 + min(mk, rm) + k, q, 0, plan);
                    if (k >= H) e.x = NO_TILE;
                    sts128(sb + OFF_TAB + 16 * (j0 + lane), e);
                }
                __syncwarp();
                if (lane == 0) mbar_arrive(sb + OFF_PLAN);
            }
        } else {
            asm volatile("barrier.cluster.arrive.relaxed.aligned;" ::: "memory");
            if (warp == 12) { e0 = entry_w(cid, 0, 0, 0); e1 = entry_w(cid, 1, 1, 0); }
            if (rank < 2 && warp >= 14) {
                const int d = lag(pl, (const uint8_t*)((uintptr_t)pl ^ 4096), sb + OFF_INFO + 16 + 4 * (warp & 1), tp);
                if (warp == 14 && lane == 0) sts32(sb + OFF_INFO + 24, d);
                asm volatile("bar.sync 11, 64;" ::: "memory");
                const int side = d > (int)lds32v(sb + OFF_INFO + 24);
                if (warp == 15 && lane == 0) asm volatile("red.relaxed.gpu.global.add.u64 [%0], %1;" :: "l"(rank ? &g_plan.x : &g_plan.y), "l"((1ull << 56) | (unsigned long long)side << cid) : "memory");
            }
            asm volatile("barrier.cluster.wait.aligned;" ::: "memory");
            if (warp >= 13) {
                if (warp == 15 && rank == 0) {
                    const uint4 inf = wait_plan();
                    if (lane == 0) sts128(sb + OFF_INFO, inf);
                    else if (lane < CL)
                        asm volatile("st.async.weak.shared::cluster.mbarrier::complete_tx::bytes.v4.u32 [%0], {%1, %2, %3, %4}, [%5];"
                                     :: "r"(mapa(sb + OFF_INFO, lane)), "r"(inf.x), "r"(inf.y), "r"(inf.z), "r"(inf.w), "r"(mapa(sb + OFF_PLAN, lane)) : "memory");
                }
                if (rank == 0) asm volatile("bar.sync 15, 96;" ::: "memory"); else mbar_wait(sb + OFF_PLAN, 0);
                const uint4 inf = lds128v(sb + OFF_INFO);
                const unsigned long long plan = inf.x | ((unsigned long long)inf.y << 32);
                const int nh = helpers(p, plan, inf.z & 1), rm = p.rm[nh], nc = inf.z >> 16;
                const uint32_t ratio = p.ratio[nh];
                if (warp == 15 && rank == 0) {
                    const int m = ((inf.z >> 8) & 0xFF) + min(lane, NSTAT - 1) * nc;
                    sts128(sb + OFF_TAB + 16 * m, cl_entry(p, m, inf.z & 1, ratio, plan));
                    __syncwarp();
                    if (lane == 0) { mbar_arrive(sb + OFF_PLAN); mbar_expect_tx(sb + OFF_PLAN2, 16 * (rm - NSTAT * nc)); }
                }
                const uint32_t rtab = mapa(sb + OFF_TAB, 0), rbar = mapa(sb + OFF_PLAN2, 0);
                for (int m0 = NSTAT * nc + 96 * (2 - rank); __any_sync(~0u, m0 < rm); m0 += 288) {
                    const int m = m0 + tid - (NCONS + 32);
                    const uint4 e = cl_entry(p, m, inf.z & 1, ratio, plan);
                    if (m < rm) asm volatile("st.async.weak.shared::cluster.mbarrier::complete_tx::bytes.v4.u32 [%0], {%1, %2, %3, %4}, [%5];"
                                             :: "r"(rtab + 16 * m), "r"(e.x), "r"(e.y), "r"(e.z), "r"(e.w), "r"(rbar) : "memory");
                }
            }
        }
        if (warp == 12) {
            if (!HELPER && rank != 0) {
                mbar_wait(sb + OFF_PLAN, 0);
                const uint4 inf = lds128v(sb + OFF_INFO);
                const unsigned long long plan = inf.x | ((unsigned long long)inf.y << 32);
                auto cell = [&](int c, int q) {
                    const int y = 32 * c - 2 + 4 * ((__popc(c & 0xB) ^ (int)(plan >> (c >> 5)) ^ q) & 1);
                    asm volatile("{\n.reg .pred p;\nelect.sync _|p, 0xffffffff;\n@p cp.async.bulk.prefetch.tensor.3d.L2.global.tile [%0, {%1, %2, %1}];\n}" :: "l"(&maps.pf), "r"(0), "r"(y) : "memory");
                };
                const int fe0 = frontier(p, 0), step = 2 * (inf.z >> 16);
                int u0 = p.c0 + 2 * ((inf.z >> 8) & 0xFF) + rank - 1;
                {
                    uint32_t t, due;
                    asm volatile("mov.u32 %0, %%clock;" : "=r"(due) :: "memory");
                    due += (PACE * (u0 - p.c0)) / step;
                    for (; __any_sync(~0u, u0 < fe0); u0 += step, due += PACE) {
                        do { asm volatile("mov.u32 %0, %%clock;" : "=r"(t) :: "memory"); } while (__any_sync(~0u, (int)(t - due) < 0));
                        cell(u0, inf.z & 1);
                    }
                }
                for (int j = XEARLY + rank - 1;; j += 2) {
                    uint4 v; uint32_t ahead;
                    for (int n = 0; __any_sync(~0u, (ahead = (((v = lds128v(tk + ((j & 7) << 4))).x >> 20) - (j + 1)) & 0xFFF) >= 0x800); n++) {
                        if (__any_sync(~0u, lds32v(tk + (((j - 1) & 7) << 4)) == (NO_TILE | (uint32_t)j << 20))) { v.x = NO_TILE; break; }
                        __nanosleep(100); fail_if(n > (1 << 24));
                    }
                    if (__any_sync(~0u, (v.x & NO_TILE) == NO_TILE)) break;
                    j += __reduce_max_sync(~0u, ahead);
                    for (int u = v.w & 0xFFFF; __any_sync(~0u, u < (v.w & 0xFFFF) + (v.w >> 16)); u++) cell(u, (v.x >> 17) & 1);
                }
            } else {
                const uint32_t rtk = HELPER ? tk : mapa(tk, lane < CL ? lane : 0), rfull = HELPER ? bar_full : mapa(bar_full, lane < CL ? lane : 0);
                int s = 0; uint32_t ph = 1;
                uint64_t pol;
                if (!HELPER) asm volatile("createpolicy.fractional.L2::evict_first.b64 %0, 1.0;" : "=l"(pol));
                else asm volatile("createpolicy.fractional.L2::evict_normal.b64 %0, 1.0;" : "=l"(pol));
                auto request = [&](int j, const uint4& t) {
                    const bool valid = t.x != NO_TILE;
                    const CUtensorMap* tm = &maps.x[(t.x >> 14) & 1];
                    mbar_wait(bar_empty + 8 * s, ph);
                    if (__any_sync(~0u, valid)) {
                        const uint32_t dst = sb + OFF_X + s * TILE_BYTES;
                        if (HELPER)
                            asm volatile("{\n.reg .pred p;\nelect.sync _|p, 0xffffffff;\n"
                                         "@p cp.async.bulk.tensor.4d.shared::cluster.global.mbarrier::complete_tx::bytes.L2::cache_hint [%0], [%4, {%6, %7, %6, %6}], [%5], %11;\n"
                                         "@p cp.async.bulk.tensor.4d.shared::cluster.global.mbarrier::complete_tx::bytes.L2::cache_hint [%1], [%4, {%6, %8, %6, %6}], [%5], %11;\n"
                                         "@p cp.async.bulk.tensor.4d.shared::cluster.global.mbarrier::complete_tx::bytes.L2::cache_hint [%2], [%4, {%6, %9, %6, %6}], [%5], %11;\n"
                                         "@p cp.async.bulk.tensor.4d.shared::cluster.global.mbarrier::complete_tx::bytes.L2::cache_hint [%3], [%4, {%6, %10, %6, %6}], [%5], %11;\n}\n"
                                         :: "r"(dst), "r"(dst + 9216), "r"(dst + 2 * 9216), "r"(dst + 3 * 9216), "l"(tm), "r"(bar_full + 8 * s), "r"(0),
                                            "r"(t.y & 0xFFFF), "r"(t.y >> 16), "r"(t.z & 0xFFFF), "r"(t.z >> 16), "l"(pol) : "memory");
                        else
                            asm volatile("{\n.reg .pred p;\nelect.sync _|p, 0xffffffff;\n"
                                         "@p cp.async.bulk.tensor.4d.shared::cluster.global.mbarrier::complete_tx::bytes.multicast::cluster.L2::cache_hint [%0], [%4, {%6, %7, %6, %6}], [%5], %11, %12;\n"
                                         "@p cp.async.bulk.tensor.4d.shared::cluster.global.mbarrier::complete_tx::bytes.multicast::cluster.L2::cache_hint [%1], [%4, {%6, %8, %6, %6}], [%5], %11, %12;\n"
                                         "@p cp.async.bulk.tensor.4d.shared::cluster.global.mbarrier::complete_tx::bytes.multicast::cluster.L2::cache_hint [%2], [%4, {%6, %9, %6, %6}], [%5], %11, %12;\n"
                                         "@p cp.async.bulk.tensor.4d.shared::cluster.global.mbarrier::complete_tx::bytes.multicast::cluster.L2::cache_hint [%3], [%4, {%6, %10, %6, %6}], [%5], %11, %12;\n}\n"
                                         :: "r"(dst), "r"(dst + 9216), "r"(dst + 2 * 9216), "r"(dst + 3 * 9216), "l"(tm), "r"(bar_full + 8 * s), "r"(0),
                                            "r"(t.y & 0xFFFF), "r"(t.y >> 16), "r"(t.z & 0xFFFF), "r"(t.z >> 16), "h"((uint16_t)((1u << CL) - 1)), "l"(pol) : "memory");
                    }
                    if (HELPER) {
                        if (lane == 0) { sts128(tk + ((j & 7) << 4), t); mbar_expect_tx(bar_full + 8 * s, valid ? TILE_BYTES : 0); }
                    } else if (lane < CL) {
                        asm volatile("mbarrier.arrive.expect_tx.shared::cluster.b64 _, [%0], %1;" :: "r"(rfull + 8 * s), "r"(valid ? TILE_BYTES + 16 : 16) : "memory");
                        asm volatile("st.async.weak.shared::cluster.mbarrier::complete_tx::bytes.v4.u32 [%0], {%1, %2, %3, %4}, [%5];"
                                     :: "r"(rtk + ((j & 7) << 4)), "r"(t.x | ((uint32_t)(j + 1) << 20)), "r"(t.y), "r"(t.z), "r"(t.w), "r"(rfull + 8 * s) : "memory");
                    }
                    if (++s == NSLOT) { s = 0; ph ^= 1; }
                };
                if (HELPER) {
#pragma unroll 1
                    for (int j = 0; j < XEARLY; j++) request(j, entry_w(p.ncl + cid + (j >> 1) * (p.ncl + p.nh), j & 1, j & 1, 0));
                    mbar_wait(sb + OFF_PLAN, 0);
                    mbar_wait(sb + OFF_GO, 0);
                    for (int j = XEARLY;; j++) {
                        const uint4 t = lds128v(sb + OFF_TAB + 16 * (j - XEARLY));
                        request(j, t);
                        if (__any_sync(~0u, t.x == NO_TILE)) break;
                    }
                } else {
                    static_assert(XEARLY == 2, "");
                    request(0, e0);
                    request(1, e1);
                    mbar_wait(sb + OFF_PLAN, 0);
                    const uint4 inf = lds128v(sb + OFF_INFO);
                    const unsigned long long plan = inf.x | ((unsigned long long)inf.y << 32);
                    const int side = inf.z & 1, nc = inf.z >> 16;
                    const int nh = helpers(p, plan, side), rm = p.rm[nh], rmo = p.rm[p.nh - nh];
                    const uint32_t ratio = p.ratio[nh], ratioo = p.ratio[p.nh - nh];
                    const int st = NSTAT * nc, sto = NSTAT * (p.ncl - nc);
                    uint4 t = lds128v(sb + OFF_TAB + 16 * ((inf.z >> 8) & 0xFF));
                    mbar_wait(sb + OFF_GO, 0);
                    int j = XEARLY;
#pragma unroll 1
                    for (; j < XEARLY + NSTAT - 2; j++) {
                        const uint4 tn = lds128v(sb + OFF_TAB + 16 * (((inf.z >> 8) & 0xFF) + (j + 1 - XEARLY) * nc));
                        request(j, t);
                        t = tn;
                    }
                    uint32_t drawn = 0;
                    int q = side;
                    request(j++, t);
                    draw(drawn, &g_ticket, 1u << (16 * side));
                    t = lds128v(sb + OFF_TAB + 16 * (((inf.z >> 8) & 0xFF) + (NSTAT - 1) * nc));
                    mbar_wait(sb + OFF_PLAN2, 0);
                    for (;; j++) {
                        request(j, t);
                        uint32_t v = __reduce_max_sync(~0u, drawn);
                        int m = st + ((v >> (16 * side)) & 0xFFFF), mo = sto + ((v >> (16 - 16 * side)) & 0xFFFF);
                        if (q == side ? m >= rm && mo < rmo : mo >= rmo && m < rm) {
                            q ^= 1;
                            draw(drawn, &g_ticket, 1u << (16 * q));
                            v = __reduce_max_sync(~0u, drawn);
                            m = st + ((v >> (16 * side)) & 0xFFFF); mo = sto + ((v >> (16 - 16 * side)) & 0xFFFF);
                        }
                        if (q == side ? m >= rm : mo >= rmo) break;
                        const bool own = q == side;
                        q = m + ((m * ratio) >> 16) > mo + ((mo * ratioo) >> 16) + DELTA ? side ^ 1 : side;
                        draw(drawn, &g_ticket, 1u << (16 * q));
                        if (own) t = lds128v(sb + OFF_TAB + 16 * m);
                        else t = cl_entry(p, mo, side ^ 1, ratioo, plan);
                    }
                    t.x = NO_TILE;
                    request(j + 1, t);
                    if (lane == 0 && atomicInc(&g_done, p.ncl - 1) == (uint32_t)p.ncl - 1) g_ticket = 0;
                }
            }
        } else {
            const int g = warp - 13;
            uint64_t spol;
            asm volatile("createpolicy.fractional.L2::evict_first.b64 %0, 1.0;" : "=l"(spol));
            mbar_wait(sb + OFF_GO, 0);
            if (g == 2 && lane == 0 && atomicInc(&g_passed, p.nctas - 1) == (uint32_t)p.nctas - 1) {
#pragma unroll
                for (int m = 0; m < 36; m++) g_ready[m * 32] = 0;
                g_plan = make_ulonglong2(0, 0);
            }
            __syncwarp();
            for (int i = 0;; i++) {
                asm volatile("bar.arrive %0, 160;" :: "r"(12 + g) : "memory");
                asm volatile("bar.sync %0, 160;" :: "r"(1 + g) : "memory");
                const uint4 t = lds128v(tk + ((i & 7) << 4));
                if ((t.x & NO_TILE) == NO_TILE) break;
                const CUtensorMap* tm = &maps.o[(t.x >> 14) & 1];
                const int row[4] = {(int)(t.y & 0xFFFF), (int)(t.y >> 16), (int)(t.z & 0xFFFF), (int)(t.z >> 16)};
                if (lane == 0) {
#pragma unroll
                    for (int k = 0; k < 4; k++)
                        asm volatile("cp.async.bulk.tensor.3d.global.shared::cta.bulk_group.L2::cache_hint [%0, {%2, %3, %4}], [%1], %5;"
                                     :: "l"(tm), "r"(sb + OFF_STG + g * STG_BYTES + k * 1024), "r"((g * 3 + rank) * 64), "r"(row[k]), "r"(0), "l"(spol) : "memory");
                    asm volatile("cp.async.bulk.commit_group;" ::: "memory");
                    asm volatile("cp.async.bulk.wait_group.read 0;" ::: "memory");
                }
                __syncwarp();
            }
        }
        __syncwarp();
        if (!HELPER) asm volatile("barrier.cluster.arrive.relaxed.aligned;\nbarrier.cluster.wait.aligned;" ::: "memory");
    } else {
        asm volatile("setmaxnreg.inc.sync.aligned.u32 160;");
        const int wg = warp >> 2, wtid = tid & 127;
        if (HELPER) asm volatile("bar.sync 0;" ::: "memory");
        else {
            int prb = cid;
            if (prb >= 36) asm volatile("barrier.cluster.wait.aligned;" ::: "memory");
#pragma unroll 1
            for (int round = 0; prb < 36; prb += p.ncl, round++) {
                const uint32_t wsm = sb + OFF_WST, msk = sb + OFF_MSK + (round & 1) * 288, mbar = sb + OFF_MBAR + (round & 1) * 8;
                if (round) {
                    asm volatile("bar.sync 3, 384;" ::: "memory");
                    if (tid == 0) mbar_expect_tx(mbar, 36 * 8);
                    prep_load(prb >> 2);
                }
                const int nt = ties(wv[0].x, wv[1].x, wv[2].x, wv[3].x) + ties(wv[0].y, wv[1].y, wv[2].y, wv[3].y) +
                               ties(wv[0].z, wv[1].z, wv[2].z, wv[3].z) + ties(wv[0].w, wv[1].w, wv[2].w, wv[3].w);
                const uint32_t mk = __ballot_sync(~0u, nt > 0), md = __ballot_sync(~0u, nt > 1);
                if (round == 0) asm volatile("barrier.cluster.wait.aligned;" ::: "memory");
                if (lane < CL)
                    asm volatile("st.async.weak.shared::cluster.mbarrier::complete_tx::bytes.v2.u32 [%0], {%1, %2}, [%3];"
                                 :: "r"(mapa(msk + (rank * 12 + warp) * 8, lane)), "r"(mk), "r"(md), "r"(mapa(mbar, lane)) : "memory");
#pragma unroll
                for (int j = 0; j < 4; j++) {
                    const int row = wrow + j;
                    const uint32_t ad = wsm + row * 128 + (((lane >> 2) ^ ((row & 1) | ((row >> 1) & 6))) << 4);
                    asm volatile("st.shared.v4.b32 [%0], {%1,%2,%3,%4};" :: "r"(ad), "r"(wv[j].x), "r"(wv[j].y), "r"(wv[j].z), "r"(wv[j].w) : "memory");
                }
                if (warp == 0) {
                    mbar_wait(mbar, (round >> 1) & 1);
                    uint4 ms = make_uint4(0, 0, 0, 0);
                    if (lane < KSTEPS) ms = lds128v(msk + 16 * lane);
                    const uint32_t te = (ms.x & 0x0F0F0F0Fu) | ((ms.z & 0x0F0F0F0Fu) << 4), to = ((ms.x >> 4) & 0x0F0F0F0Fu) | (ms.z & 0xF0F0F0F0u);
                    const uint32_t de = (ms.y & 0x0F0F0F0Fu) | ((ms.w & 0x0F0F0F0Fu) << 4), dq = ((ms.y >> 4) & 0x0F0F0F0Fu) | (ms.w & 0xF0F0F0F0u);
                    auto count = [](uint32_t v) { v -= (v >> 1) & 0x55555555u; v = (v & 0x33333333u) + ((v >> 2) & 0x33333333u); return (v + (v >> 4)) & 0x0F0F0F0Fu; };
                    const uint32_t c0 = __reduce_add_sync(~0u, count(te)), c1 = __reduce_add_sync(~0u, count(to));
                    auto byte = [](uint32_t a, uint32_t b, uint32_t u) { return __byte_perm(a, b, (u >> 1) + 4 * (u & 1)) & 0xFFu; };
                    const uint32_t ku = byte(c0, c1, lane & 7) * 8 + (lane & 7), k2 = 2 * (lane >> 3);
                    const uint32_t ranks = __reduce_add_sync(~0u, ((byte(c0, c1, k2) * 8 + k2 < ku) + (byte(c0, c1, k2 + 1) * 8 + k2 + 1 < ku)) << (4 * (lane & 7)));
                    const uint32_t order = __reduce_add_sync(~0u, lane < 8 ? lane << (4 * ((ranks >> (4 * lane)) & 7)) : 0);
                    int cnt[4]; uint32_t mq = 0;
#pragma unroll
                    for (int z = 0; z < 4; z++) {
                        const uint32_t ua = (order >> (4 * z)) & 7, ub = (order >> (28 - 4 * z)) & 7;
                        const uint32_t ta = byte(te, to, ua), tb = byte(te, to, ub), v = ta | tb | ((ta & tb) | byte(de, dq, ua) | byte(de, dq, ub)) << 8;
                        cnt[z] = __popc(v);
                        if (z == (prb & 3)) mq = v;
                    }
                    const uint32_t l01 = __reduce_add_sync(~0u, cnt[0] | cnt[1] << 16), l23 = __reduce_add_sync(~0u, cnt[2] | cnt[3] << 16);
                    const int ulo = (order >> (4 * (prb & 3))) & 7, uhi = (order >> (28 - 4 * (prb & 3))) & 7;
                    const int full = max(max(max((int)(l01 & 0xFFFF) - cnt[0], (int)(l01 >> 16) - cnt[1]), max((int)(l23 & 0xFFFF) - cnt[2], (int)(l23 >> 16) - cnt[3])), 16);
                    const int twice = __reduce_min_sync(~0u, lane < KSTEPS ? full << 12 | (65 - cnt[0] - cnt[1] - cnt[2] - cnt[3]) << 5 | lane : full << 12 | 31) & 31;
                    sts32(sb + OFF_SEL + 4 * lane, lane == 31 ? ulo | (uhi << 4) | (twice << 8) : lane == twice ? 0 : mq);
                }
                asm volatile("bar.sync 1, 384;" ::: "memory");
                const uint32_t units = lds32v(sb + OFF_SEL + 4 * 31), mq = lds32v(sb + OFF_SEL + 4 * min(lane, 30));
                uint32_t wm[4];
                load_units(wsm, warp, units & 7, (units >> 4) & 7, lane, wm);
                emit_half(wm, mq, prb, rank * 6 + (warp >> 1), warp & 1, lane, units, b0, b1);
                asm volatile("bar.sync 2, 384;" ::: "memory");
                if (tid == 0) asm volatile("red.release.gpu.global.add.u32 [%0], 1;" :: "l"(&g_ready[prb * 32]) : "memory");
            }
            if (warp == 0 && lane < CL) mbar_arrive_cluster(mapa(sb + OFF_GO, lane));
        }
        const int mt = wg * 3 + rank, rb = mt * 4 + (warp & 3);
        {
            uint32_t v; int n = 0;
            do { asm volatile("ld.acquire.gpu.global.u32 %0, [%1];" : "=r"(v) : "l"(&g_ready[rb * 32]) : "memory"); fail_if(++n > (1 << 22)); } while (__any_sync(~0u, v < CL));
        }
        if (wg > 0) asm volatile("bar.sync %0, 256;" :: "r"(7 + wg) : "memory");
        uint32_t a[KSTEPS + 1][4], meta[9];
        uint2 rv[3]; uint32_t ro[3], sel[3];
        uint32_t info, bias_lo, bias_hi;
        {
            const uint4* ap = g_aux + rb * 6 * 32 + lane;
            const uint4 v3 = ldw(ap + 96), v2 = ldw(ap + 64), v4 = ldw(ap + 128), v5 = ldw(ap + 160), v0 = ldw(ap), v1 = ldw(ap + 32);
            meta[0] = v0.x; meta[1] = v0.y; meta[2] = v0.z; meta[3] = v0.w; meta[4] = v1.x; meta[5] = v1.y; meta[6] = v1.z; meta[7] = v1.w;
            meta[8] = v2.x; info = v2.y; bias_lo = v2.z; bias_hi = v2.w;
            ro[0] = v3.x; ro[1] = v3.y; ro[2] = v3.z;
            rv[0] = make_uint2(v4.x, v4.y); rv[1] = make_uint2(v4.z, v4.w); rv[2] = make_uint2(v5.x, v5.y);
        }
#pragma unroll
        for (int k = 0; k < KSTEPS + 1; k++) { uint4 v = ldw(&g_afrag[(mt * (KSTEPS + 1) + k) * 128 + wtid]); a[k][0] = v.x; a[k][1] = v.y; a[k][2] = v.z; a[k][3] = v.w; }
        if (wg < 2) asm volatile("bar.arrive %0, 256;" :: "r"(8 + wg) : "memory");
        if (lane == 0) mbar_arrive(sb + OFF_GO);
        auto selector = [](uint32_t o) { return 0x5410u + ((o >> 15) & 1) * 0x22u + (o >> 31) * 0x2200u; };
#pragma unroll
        for (int j = 0; j < 3; j++) { sel[j] = selector(ro[j]); ro[j] &= 0x7FFF7FFFu; }
        mbar_wait(bar_full, 0);
        info = __shfl_sync(~0u, info, 0);
        const int ngrp = info & 0xFF, ulo = (info >> 8) & 7, uhi = (info >> 12) & 7;
        const uint32_t stg = sb + OFF_STG + wg * STG_BYTES + ((lane >> 4) * 8 + (lane & 7)) * 128 + (((((lane >> 3) & 1) ? uhi : ulo) ^ (lane & 7)) << 4);
        const uint32_t twice = (((info >> 17) & 15) * 1024 + ((info >> 16) & 1) * 64) >> 4;
        const uint32_t rempty = HELPER ? bar_empty : mapa(bar_empty, 0);
        float acc[NACC];
        uint32_t bq[NB][6];
        auto gather = [&](uint32_t xb) {
#pragma unroll
            for (int j = 0; j < 4; j++) {
                const uint32_t o = xb + ((j & 1) ? ro[j >> 1] >> 16 : ro[j >> 1] & 0xFFFF);
#pragma unroll
                for (int n = 0; n < NB; n++) {
                    bq[n][j] = 0;
                    asm volatile("{\n.reg .pred p;\nsetp.lt.s32 p, %2, %3;\n@p ld.shared.b32 %0, [%1];\n}" : "+r"(bq[n][j]) : "r"(o + n * 9216), "r"(j), "r"(ngrp) : "memory");
                }
            }
        };
        auto select = [&]() {
#pragma unroll
            for (int n = 0; n < NB; n++)
#pragma unroll
                for (int j = 0; j < 2; j++) bq[n][2 * j] = __byte_perm(bq[n][2 * j], bq[n][2 * j + 1], sel[j]);
        };
        auto further = [&](uint32_t xb, int bar) {
#pragma unroll 1
            for (int y = 4; y < min(ngrp, 5); y++) {
#pragma unroll
                for (int n = 0; n < NB; n++) { bq[n][4] = lds32(xb + (ro[2] & 0xFFFF) + n * 9216); bq[n][5] = lds32(xb + (ro[2] >> 16) + n * 9216); }
#pragma unroll
                for (int n = 0; n < NB; n++) mma_k8(acc + 4 * n, rv[2], __byte_perm(bq[n][4], bq[n][5], sel[2]));
                if (bar >= 0) asm volatile("bar.arrive %0, 256;" :: "r"(bar) : "memory");
#pragma unroll 1
                for (int z = 3; 2 * z < ngrp; z++) {
                    const uint2 v = __ldca(&g_rval[(rb * 36 + z) * 32 + lane]); const uint32_t off = __ldca(&g_roff[(rb * 36 + z) * 32 + lane]);
                    uint32_t bx[NB];
#pragma unroll
                    for (int n = 0; n < NB; n++) bx[n] = __byte_perm(lds32(xb + (off & 0x7FFF) + n * 9216), lds32(xb + ((off >> 16) & 0x7FFF) + n * 9216), selector(off));
#pragma unroll
                    for (int n = 0; n < NB; n++) mma_k8(acc + 4 * n, v, bx[n]);
                }
            }
        };
        bool more = true;
#pragma unroll
        for (int n = 0; n < NB; n++) bq[n][4] = bq[n][5] = 0;
        gather(sb + OFF_X);
        select();
#pragma unroll
        for (int n = 0; n < NB; n++) mma_k16(acc + 4 * n, rv[0], rv[1], bq[n][0], bq[n][2], 0.f, 0.f, 0.f, 0.f);
        further(sb + OFF_X, -1);
        const int bar_a = 8 + wg, bar_an = 8 + (wg + 2) % 3, bar_tn = 4 + (wg + 2) % 3;
        if (wg == 1) asm volatile("bar.arrive 4, 256;" ::: "memory");
        if (wg == 2) { asm volatile("bar.sync 10, 256;" ::: "memory"); asm volatile("bar.arrive 5, 256;" ::: "memory"); }
        auto run = [&](auto tw) {
        constexpr bool TW = decltype(tw)::value;
        int s = 0; uint32_t ph = 0;
        bool ready = false;
        for (int i = 0; more; i++) {
            const uint32_t xb = sb + OFF_X + s * TILE_BYTES;
            const int s1 = s + 1 == NSLOT ? 0 : s + 1;
            const uint32_t ph1 = s1 == 0 ? ph ^ 1 : ph;
            asm volatile("bar.sync %0, 256;" :: "r"(4 + wg) : "memory");
            const uint64_t desc = ((uint64_t)1 << 62) | ((uint64_t)(9216 >> 4) << 32) | ((uint64_t)1 << 16) | (uint64_t)(xb >> 4);
            asm volatile("wgmma.fence.sync.aligned;" ::: "memory");
#pragma unroll
            for (int k = 0; k < KSTEPS; k++) {
                const uint64_t d = desc + (uint64_t)(((k >> 1) * 1024 + (k & 1) * 64) >> 4);
                if (k & 1) wgmma_sp<1>(acc, a[k], d, meta[k >> 1]);
                else       wgmma_sp<0>(acc, a[k], d, meta[k >> 1]);
            }
            if (TW) wgmma_sp<0>(acc, a[KSTEPS], desc + twice, 0x44444444u);
            asm volatile("wgmma.commit_group.sync.aligned;" ::: "memory");
            asm volatile("bar.arrive %0, 256;" :: "r"(bar_an) : "memory");
            if (!ready) mbar_wait(bar_full + 8 * s1, ph1);
            const uint32_t tn = lds32v(tk + (((i + 1) & 7) << 4));
            gather(sb + OFF_X + s1 * TILE_BYTES);
            asm volatile("bar.sync %0, 160;" :: "r"(12 + wg) : "memory");
            asm volatile("wgmma.wait_group.sync.aligned 0;" ::: "memory");
            if (wtid == 0) { if (HELPER) mbar_arrive(bar_empty + 8 * s); else mbar_arrive_cluster(rempty + 8 * s); }
#pragma unroll
            for (int n = 0; n < NB; n += 2) {
                const uint32_t p0 = pack_bias(acc[4 * n], acc[4 * n + 1], bias_lo), p1 = pack_bias(acc[4 * n + 2], acc[4 * n + 3], bias_hi);
                const uint32_t p2 = pack_bias(acc[4 * n + 4], acc[4 * n + 5], bias_lo), p3 = pack_bias(acc[4 * n + 6], acc[4 * n + 7], bias_hi);
                if (n == 0) asm volatile("stmatrix.sync.aligned.m8n8.x4.trans.shared.b16 [%0], {%1,%2,%3,%4};" :: "r"(stg + n * 1024), "r"(p0), "r"(p1), "r"(p2), "r"(p3) : "memory");
                else asm volatile("{\n.reg .pred p;\nAGAIN:\nstmatrix.sync.aligned.m8n8.x4.trans.shared.b16 [%0], {%1,%2,%3,%4};\nsetp.eq.u32 p, %5, 0xFFFFFFFE;\n@p bra.uni AGAIN;\n}"
                                  :: "r"(stg + n * 1024), "r"(p0), "r"(p1), "r"(p2), "r"(p3), "r"(info) : "memory");
            }
            more = __any_sync(~0u, (tn & NO_TILE) != NO_TILE);
            select();
            if (wg != 2 || more) {
                asm volatile("{\n.reg .pred p;\nTURN:\nbar.sync %0, 256;\nsetp.eq.u32 p, %1, 0xFFFFFFFF;\n@p bra.uni TURN;\n}" :: "r"(bar_a), "r"(info) : "memory");
#pragma unroll
                for (int n = 0; n < NB; n++) {
                    mma_k16(acc + 4 * n, rv[0], rv[1], bq[n][0], bq[n][2], 0.f, 0.f, 0.f, 0.f);
                    if (n == 0) asm volatile("{\n.reg .pred p;\nsetp.le.s32 p, %1, 4;\n@p bar.arrive %0, 256;\n}" :: "r"(bar_tn), "r"(ngrp) : "memory");
                }
                further(sb + OFF_X + s1 * TILE_BYTES, bar_tn);
            }
            asm volatile("fence.proxy.async.shared::cta;" ::: "memory");
            asm volatile("bar.arrive %0, 160;" :: "r"(1 + wg) : "memory");
            s = s1; ph = ph1;
            ready = __all_sync(~0u, mbar_test(bar_full + 8 * (s + 1 == NSLOT ? 0 : s + 1), s + 1 == NSLOT ? ph ^ 1 : ph));
        }
        };
        if (((info >> 16) & 31) < KSTEPS) run(Flag<true>()); else run(Flag<false>());
        if (wg == 0) asm volatile("bar.sync 4, 256;" ::: "memory");
        asm volatile("bar.sync %0, 160;" :: "r"(12 + wg) : "memory");
        asm volatile("bar.arrive %0, 160;" :: "r"(1 + wg) : "memory");
        if (!HELPER) asm volatile("barrier.cluster.arrive.relaxed.aligned;\nbarrier.cluster.wait.aligned;" ::: "memory");
    }
}

typedef CUresult (*EncodeFn)(CUtensorMap*, CUtensorMapDataType, cuuint32_t, void*, const cuuint64_t*, const cuuint64_t*, const cuuint32_t*, const cuuint32_t*,
                             CUtensorMapInterleave, CUtensorMapSwizzle, CUtensorMapL2promotion, CUtensorMapFloatOOBfill);

__global__ void plain_kernel(const __nv_bfloat16* x, const __nv_bfloat16* w, const __nv_bfloat16* b, __nv_bfloat16* out, int ntok) {
    const int t0 = blockIdx.x * 8;
    for (int f = threadIdx.x; f < D; f += blockDim.x) {
        float acc[8] = {};
        for (int g = 0; g < D / 4; g++) {
            float v[4], m[4];
            for (int i = 0; i < 4; i++) { v[i] = __bfloat162float(w[(4 * g + i) * D + f]); m[i] = fabsf(v[i]); }
            const float thr = fmaxf(fminf(fmaxf(m[0], m[1]), fmaxf(m[2], m[3])), fmaxf(fminf(m[0], m[1]), fminf(m[2], m[3])));
            for (int i = 0; i < 4; i++)
                for (int t = 0; t < 8; t++)
                    if (m[i] >= thr && t0 + t < ntok) acc[t] += v[i] * __bfloat162float(x[(size_t)(t0 + t) * D + 4 * g + i]);
        }
        for (int t = 0; t < 8; t++)
            if (t0 + t < ntok) out[(size_t)(t0 + t) * D + f] = __hadd(__float2bfloat16(acc[t]), b[f]);
    }
}

extern "C" void kernel_launch(void* const* d_in, const int* in_sizes, int n_in, void* d_out, int out_size) {
    static EncodeFn enc = nullptr;
    static int ncl = 0, nhelp = 0;
    const int ntok = in_sizes[0] / D;
    cudaLaunchConfig_t cfg = {};
    cudaLaunchAttribute at[1];
    at[0].id = cudaLaunchAttributeClusterDimension; at[0].val.clusterDim.x = CL; at[0].val.clusterDim.y = 1; at[0].val.clusterDim.z = 1;
    cfg.blockDim = dim3(NTHREADS); cfg.dynamicSmemBytes = SMEM_BYTES; cfg.attrs = at; cfg.numAttrs = 1; cfg.stream = cudaStreamPerThread;
    if (!enc) {
        cudaDriverEntryPointQueryResult qr; void* fn = nullptr;
        cudaGetDriverEntryPoint("cuTensorMapEncodeTiled", &fn, cudaEnableDefault, &qr);
        enc = (EncodeFn)fn;
        cudaFuncSetAttribute(spgemm_kernel<false>, cudaFuncAttributeMaxDynamicSharedMemorySize, SMEM_BYTES);
        cudaFuncSetAttribute(spgemm_kernel<true>, cudaFuncAttributeMaxDynamicSharedMemorySize, SMEM_BYTES);
        int dev = 0, nsm = 0;
        cudaGetDevice(&dev);
        cudaDeviceGetAttribute(&nsm, cudaDevAttrMultiProcessorCount, dev);
        cfg.gridDim = dim3(CL * (nsm / CL));
        cudaOccupancyMaxActiveClusters(&ncl, spgemm_kernel<false>, &cfg);
        if (ncl < 1) ncl = 1;
        nhelp = nsm > CL * ncl ? (nsm - CL * ncl) / CL : 0;
        if (nhelp > 7) nhelp = 7;
    }
    if (ntok % 4096 || ntok < 16384 || ntok > 65536 || ncl < 2 || ncl > 56 || 8 * (ncl + nhelp) > ntok / 64) {
        plain_kernel<<<(ntok + 7) / 8, 192, 0, cudaStreamPerThread>>>((const __nv_bfloat16*)d_in[0], (const __nv_bfloat16*)d_in[1], (const __nv_bfloat16*)d_in[2], (__nv_bfloat16*)d_out, ntok);
        return;
    }
    Maps maps;
    for (int v = 0; v < 2; v++) {
        const cuuint32_t rows = v == 0 ? 2 : 1;
        const cuuint64_t pitch = (v == 0 ? 14 : 57) * D * 2;
        {
            cuuint64_t dims[4] = {64, (cuuint64_t)ntok, 8 / rows, 9};
            cuuint64_t strides[3] = {D * 2, pitch, 128};
            cuuint32_t box[4] = {64, rows, 8 / rows, 9}, es[4] = {1, 1, 1, 1};
            enc(&maps.x[v], CU_TENSOR_MAP_DATA_TYPE_BFLOAT16, 4, d_in[0], dims, strides, box, es, CU_TENSOR_MAP_INTERLEAVE_NONE,
                CU_TENSOR_MAP_SWIZZLE_128B, CU_TENSOR_MAP_L2_PROMOTION_L2_128B, CU_TENSOR_MAP_FLOAT_OOB_FILL_NONE);
        }
        {
            cuuint64_t dims[3] = {D, (cuuint64_t)ntok, 8 / rows};
            cuuint64_t strides[2] = {D * 2, pitch};
            cuuint32_t box[3] = {64, rows, 8 / rows}, es[3] = {1, 1, 1};
            enc(&maps.o[v], CU_TENSOR_MAP_DATA_TYPE_BFLOAT16, 3, d_out, dims, strides, box, es, CU_TENSOR_MAP_INTERLEAVE_NONE,
                CU_TENSOR_MAP_SWIZZLE_128B, CU_TENSOR_MAP_L2_PROMOTION_NONE, CU_TENSOR_MAP_FLOAT_OOB_FILL_NONE);
        }
    }
    {
        cuuint64_t dims[3] = {256, (cuuint64_t)ntok * D * 2 / 2048, 4};
        cuuint64_t strides[2] = {2048, 16384};
        cuuint32_t box[3] = {256, 4, 4}, es[3] = {1, 1, 1};
        enc(&maps.pf, CU_TENSOR_MAP_DATA_TYPE_FLOAT64, 3, d_in[0], dims, strides, box, es, CU_TENSOR_MAP_INTERLEAVE_NONE,
            CU_TENSOR_MAP_SWIZZLE_NONE, CU_TENSOR_MAP_L2_PROMOTION_NONE, CU_TENSOR_MAP_FLOAT_OOB_FILL_NONE);
    }
    Params p;
    p.w = (const uint16_t*)d_in[1]; p.bias = (const uint16_t*)d_in[2]; p.x = (const uint8_t*)d_in[0];
    p.nq = ntok / 64; p.npages = (int)(((size_t)ntok * D * 2) >> 21);
    const int nc = ncl, nh = nhelp;
    p.ncl = nc; p.nh = nh; p.nctas = CL * (nc + nh);
    p.m0 = (nc + nh) * XEARLY / 2;
    for (int h = 0; h < 8; h++) {
        const uint32_t R = p.nq - p.m0, H = h * (HT * p.nq / 1024 * 44 / (nc + nh));
        p.ratio[h] = h <= nh ? (H << 16) / (R - H) : 0;
        p.rm[h] = p.ratio[h] ? (((R - 1) << 16) + 0x7FFFu) / (0x10000u + p.ratio[h]) + 1 : R;
    }
    p.c0 = (p.m0 * 9) >> 3;
    p.tb = p.m0 + (NSLOT - XEARLY) * (nc + nh) / 2;
    p.ta = p.tb + 1 + (int)((p.nq - p.tb) * TAFRAC); p.te = (int)(p.nq * TEFRAC) + 2;
    p.slope0 = ((LEAD1 - LEAD0) << 16) / (p.ta - p.tb); p.slope1 = ((LEAD1 - LEADE) << 16) / (p.te - p.ta);
    cfg.gridDim = dim3(CL * nc);
    cudaLaunchKernelEx(&cfg, spgemm_kernel<false>, p, maps);
    if (nh) {
        at[0].id = cudaLaunchAttributeProgrammaticStreamSerialization; at[0].val.programmaticStreamSerializationAllowed = 1;
        cfg.gridDim = dim3(CL * nh);
        cudaLaunchKernelEx(&cfg, spgemm_kernel<true>, p, maps);
    }
}
```

```cpp
#include <cuda_runtime.h>
#include <cuda_bf16.h>
#include <cuda.h>
#include <stdint.h>

constexpr int D = 576;
constexpr int NT = 32;
constexpr int NSLOT = 5;
constexpr int XEARLY = 2;
constexpr int NSTAT = 4;
constexpr int DELTA = 36;
constexpr int HT = 45;
constexpr int LEAD0 = 140, LEAD1 = 295, LEADE = 32, PACE = 1200;
constexpr double TAFRAC = 0.261, TEFRAC = 0.97;
constexpr int PWAIT = 1900;
constexpr int KSTEPS = 18;
constexpr int CL = 3;
constexpr int TILE_BYTES = NT * D * 2;
constexpr int STG_BYTES = NT * 128;
constexpr int NACC = NT / 2;
constexpr int NB = NT / 8;
constexpr int NCONS = 384;
constexpr int NTHREADS = 512;
constexpr int NTAB = 1024;
constexpr uint32_t NO_TILE = 0xFFFFFu;

constexpr int OFF_X = 0;
constexpr int OFF_WST = OFF_X + (NSLOT - 1) * TILE_BYTES;
constexpr int OFF_STG = OFF_X + NSLOT * TILE_BYTES;
constexpr int OFF_TAB = OFF_STG + 3 * STG_BYTES;
constexpr int OFF_TK = OFF_TAB + 16 * NTAB;
constexpr int OFF_MSK = OFF_TK + 128;
constexpr int OFF_SEL = OFF_MSK + 2 * 36 * 8;
constexpr int OFF_INFO = OFF_SEL + 128;
constexpr int OFF_FULL = OFF_INFO + 32;
constexpr int OFF_EMPTY = OFF_FULL + 8 * NSLOT;
constexpr int OFF_MBAR = OFF_EMPTY + 8 * NSLOT;
constexpr int OFF_GO = OFF_MBAR + 16;
constexpr int OFF_PLAN = OFF_GO + 8;
constexpr int OFF_PLAN2 = OFF_PLAN + 8;
constexpr int SMEM_BYTES = OFF_PLAN2 + 8 + 1024;
static_assert(SMEM_BYTES <= 232448 && TILE_BYTES >= 192 * 128 && XEARLY % 2 == 0 && XEARLY < NSLOT && NSLOT < 8 && NB == 4 && OFF_INFO % 16 == 0, "layout");

__device__ __align__(128) uint4    g_afrag[9 * (KSTEPS + 1) * 128];
__device__ __align__(128) uint4    g_aux[36 * 6 * 32];
__device__ __align__(128) uint2    g_rval[36 * 36 * 32];
__device__ __align__(128) uint32_t g_roff[36 * 36 * 32];
__device__ __align__(128) uint32_t g_ready[36 * 32];
__device__ __align__(128) uint32_t g_passed;
__device__ __align__(128) uint32_t g_ticket;
__device__ __align__(128) uint32_t g_hreg[3 * 32];
__device__ __align__(128) uint32_t g_done;
__device__ __align__(128) ulonglong2 g_plan;

__device__ __forceinline__ uint32_t max2(uint32_t a, uint32_t b) { uint32_t d; asm("max.u16x2 %0, %1, %2;" : "=r"(d) : "r"(a), "r"(b)); return d; }
__device__ __forceinline__ uint32_t min2(uint32_t a, uint32_t b) { uint32_t d; asm("min.u16x2 %0, %1, %2;" : "=r"(d) : "r"(a), "r"(b)); return d; }
__device__ __forceinline__ uint32_t sign2(uint32_t a) { uint32_t d; asm("prmt.b32 %0, %1, %1, 0xBB99;" : "=r"(d) : "r"(a)); return d; }
__device__ __forceinline__ void load_units(uint32_t wsm, int g4, int ulo, int uhi, int lane, uint32_t (&m)[4]) {
    const int row = g4 * 16 + ((lane & 7) >> 1) * 4 + ((lane >> 3) & 1) * 2 + (lane & 1);
    const uint32_t ad = wsm + row * 128 + (((lane < 16 ? ulo : uhi) ^ ((row & 1) | ((row >> 1) & 6))) << 4);
    asm volatile("ldmatrix.sync.aligned.m8n8.x4.trans.shared.b16 {%0,%1,%2,%3}, [%4];" : "=r"(m[0]), "=r"(m[1]), "=r"(m[2]), "=r"(m[3]) : "r"(ad) : "memory");
}
__device__ __forceinline__ void zip4(uint32_t a01, uint32_t a23, uint32_t b01, uint32_t b23, uint32_t (&x)[4]) {
    x[0] = __byte_perm(a01, b01, 0x5410); x[1] = __byte_perm(a01, b01, 0x7632); x[2] = __byte_perm(a23, b23, 0x5410); x[3] = __byte_perm(a23, b23, 0x7632);
}
__device__ __forceinline__ void middle2(const uint32_t (&x)[4], uint32_t (&m)[4], uint32_t& u, uint32_t& v) {
#pragma unroll
    for (int i = 0; i < 4; i++) m[i] = x[i] & 0x7FFF7FFFu;
    u = min2(max2(m[0], m[1]), max2(m[2], m[3])); v = max2(min2(m[0], m[1]), min2(m[2], m[3]));
}
__device__ __forceinline__ int ties(uint32_t x0, uint32_t x1, uint32_t x2, uint32_t x3) {
    const uint32_t x[4] = {x0, x1, x2, x3};
    uint32_t m[4], u, v;
    middle2(x, m, u, v);
    const uint32_t t = u ^ v, f = u ^ min2(min2(m[0], m[1]), min2(m[2], m[3]));
    const bool t0 = (t & 0xFFFFu) == 0 && (v & 0xFFFFu) != 0, t1 = t < 0x10000u && v >= 0x10000u;
    return t0 + t1 + 2 * ((t0 && (f & 0xFFFFu) == 0) || (t1 && f < 0x10000u));
}
__device__ __forceinline__ void split(const uint32_t (&x)[4], bool dbl, bool P, uint32_t& alo, uint32_t& ahi, uint32_t& nib, uint32_t& va, uint32_t& vb) {
    uint32_t m[4], u, v;
    middle2(x, m, u, v);
    const uint32_t c = 0x80008000u - max2(max2(u, v), 0x00010001u);
    uint32_t k0 = sign2(m[0] + c), k1 = sign2(m[1] + c), k2 = sign2(m[2] + c), k3 = sign2(m[3] + c);
    const uint32_t three = (k0 & k1 & (k2 | k3)) | (k2 & k3 & (k0 | k1)), four = k0 & k1 & k2 & k3;
    const bool a2 = !dbl && P;
    const uint32_t pa = a2 ? k2 : k0, pb = dbl ? k2 : P ? k3 : k1;
    const uint32_t ra = three & pa, rb = three & pb & (four | ~pa);
    va = (a2 ? x[2] : x[0]) & ra; vb = (dbl ? x[2] : P ? x[3] : x[1]) & rb;
    if (a2) k2 &= ~ra; else k0 &= ~ra;
    if (dbl) k2 &= ~rb; else if (P) k3 &= ~rb; else k1 &= ~rb;
    const uint32_t s1 = k1 & k0, s2 = k2 & (k0 | k1);
    const uint32_t t = (k1 & x[1]) | (~k1 & k2 & x[2]);
    const uint32_t x0 = (k0 & x[0]) | (~k0 & t), x1 = (s1 & x[1]) | (s2 & x[2]) | (k3 & x[3]);
    nib = (~k0 & k1 & 0x00010001u) | (~k0 & ~k1 & 0x00020002u) | (~s2 & 0x00040004u) | (~s1 & 0x00080008u);
    alo = __byte_perm(x0, x1, 0x5410); ahi = __byte_perm(x0, x1, 0x7632);
}
__device__ __forceinline__ uint32_t resid_off(int g, int P, int r) {
    int k0 = 4 * g + 2 * P;
    int chunk = k0 >> 6, byte = (k0 & 63) * 2;
    return chunk * 1024 + r * 128 + (((byte >> 4) ^ r) << 4) + (byte & 15);
}
__device__ __forceinline__ void emit_half(const uint32_t (&wm)[4], uint32_t md, int rb, int ks, int e, int lane, uint32_t units, uint32_t b0, uint32_t b1) {
    uint32_t* const aux = (uint32_t*)(g_aux + rb * 6 * 32);
    auto put_slot = [&](int j, int ln, uint32_t v, uint32_t off) {
        uint16_t* o = j < 6 ? (uint16_t*)aux + (3 * 32 + ln) * 8 + j : (uint16_t*)g_roff + ((rb * 36 + (j >> 1)) * 32 + ln) * 2 + (j & 1);
        uint16_t* w = j < 6 ? (uint16_t*)aux + ((4 + (j >> 2)) * 32 + ln) * 8 + (j & 2) * 2 + (j & 1) : (uint16_t*)g_rval + ((rb * 36 + (j >> 1)) * 32 + ln) * 4 + (j & 1);
        o[0] = (uint16_t)off; w[0] = (uint16_t)v; w[2] = (uint16_t)(v >> 16);
    };
    const int r = lane >> 2, q = lane & 3, g = 4 * e + q, twice = units >> 8;
    const uint32_t gm = __shfl_sync(~0u, md, ks);
    const uint32_t c2 = __popc(md & 0x5555u) | (__popc(md & 0xAAAAu) << 16);
    const uint32_t tot = __reduce_add_sync(~0u, c2), pre = __reduce_add_sync(~0u, lane < ks ? c2 : 0u);
    const int ne = tot & 0xFFFF, no = tot >> 16;
    const int rk = ((q & 1) ? pre >> 16 : pre & 0xFFFF) + __popc(gm & ((q & 1) ? 0xAAAAu : 0x5555u) & (((1u << g) - 1) * 0x101u));
    const bool dbl = (gm >> (8 + g)) & 1;
    uint32_t a0, a1, va, vb, x[4], nib;
    zip4(wm[0], wm[1], wm[2], wm[3], x); split(x, dbl, rk & 1 && ks != twice, a0, a1, nib, va, vb);
    uint2* const frag = (uint2*)(g_afrag + (rb >> 2) * (KSTEPS + 1) * 128 + (rb & 3) * 32 + lane) + e;
    frag[ks * 256] = make_uint2(a0, a1);
    if (ks == (twice < KSTEPS ? twice : 0)) frag[KSTEPS * 256] = twice < KSTEPS ? make_uint2(__byte_perm(va, vb, 0x5410), __byte_perm(va, vb, 0x7632)) : make_uint2(0, 0);
    nib <<= 4 * q;
    nib |= __shfl_xor_sync(~0u, nib, 1);
    nib |= __shfl_xor_sync(~0u, nib, 2);
    if (q == 2 * (ks & 1) + e) aux[((ks >> 3) * 32 + lane) * 4 + ((ks >> 1) & 3)] = nib;
    const int em = min(ne, max(8, 16 - no)), om = min(no, 16 - em);
    const int odd = q & 1, m = odd ? om : em;
    auto place = [&](int k) {
        const int t = 15 - k;
        return k >= m ? 16 + (odd ? ne - em : 0) + k - m : k < 8 ? (k >> 1) * 4 + 2 * odd + (k & 1) : (t >> 1) * 4 + 2 * (odd ^ 1) + (t & 1);
    };
    const uint32_t second = (__ballot_sync(~0u, vb != 0) & (0x11111111u << q)) != 0 && !dbl;
    if ((gm >> g) & 1) {
        const int sl = place(rk);
        put_slot(sl >> 2, r * 4 + (sl & 3), !dbl ? va | vb : (rk & 1) ? vb : va, resid_off(ks * 8 + g, rk & 1, r) | (second << 15));
        if (dbl) { const int s2 = place(rk + 1); put_slot(s2 >> 2, r * 4 + (s2 & 3), (rk & 1) ? va : vb, resid_off(ks * 8 + g, ~rk & 1, r)); }
    }
    const int ntot = ne + no, z = 2 * ks + e;
    const int ng = ntot > 16 ? (ntot + 3) >> 2 : min(4, (max(ne, no) + 1) >> 1);
    if (z == 8) {
        const int ulo = units & 7, uhi = (units >> 4) & 7;
        aux[(2 * 32 + lane) * 4 + 1] = ng | (units << 8);
        *(uint2*)(aux + (2 * 32 + lane) * 4 + 2) = make_uint2(__shfl_sync(~0u, ulo < 4 ? b0 : b1, (ulo * 8 + r) & 31) * 0x10001u, __shfl_sync(~0u, uhi < 4 ? b0 : b1, (uhi * 8 + r) & 31) * 0x10001u);
        aux[(3 * 32 + lane) * 4 + 3] = 0; *(uint2*)(aux + (5 * 32 + lane) * 4 + 2) = make_uint2(0, 0);
    }
    const int idx = 2 * z + (q & 1);
    const int frow = z < 6 ? z : z == 6 ? ng - 1 : ng;
    const bool fill = z < 4 ? !(idx < ((q >> 1) ? om : em) || (15 - idx) < ((q >> 1) ? em : om))
                            : (z < 6 || (ng > 6 && (z == 6 || (z == 7 && (ng & 1))))) && 4 * frow + q >= ntot;
    if (fill) put_slot(frow, lane, 0, resid_off(q >> 1, q & 1, r));
}

template<int SEL> __device__ __forceinline__ void wgmma_sp(float (&d)[NACC], const uint32_t (&a)[4], uint64_t bdesc, uint32_t meta) {
    asm volatile("{\n.reg .pred p;\nsetp.ne.b32 p, %22, 0;\n"
        "wgmma.mma_async.sp.sync.aligned.m64n32k32.f32.bf16.bf16 {%0, %1, %2, %3, %4, %5, %6, %7, %8, %9, %10, %11, %12, %13, %14, %15}, {%16, %17, %18, %19}, %20, %21, %23, p, 1, 1, 0;\n}\n"
        : "+f"(d[0]), "+f"(d[1]), "+f"(d[2]), "+f"(d[3]), "+f"(d[4]), "+f"(d[5]), "+f"(d[6]), "+f"(d[7]), "+f"(d[8]), "+f"(d[9]), "+f"(d[10]), "+f"(d[11]), "+f"(d[12]), "+f"(d[13]), "+f"(d[14]), "+f"(d[15])
        : "r"(a[0]), "r"(a[1]), "r"(a[2]), "r"(a[3]), "l"(bdesc), "r"(meta), "r"(1), "n"(SEL));
}

__device__ __forceinline__ void mbar_init(uint32_t bar, uint32_t cnt) { asm volatile("mbarrier.init.shared::cta.b64 [%0], %1;" :: "r"(bar), "r"(cnt) : "memory"); }
__device__ __forceinline__ void mbar_expect_tx(uint32_t bar, uint32_t bytes) {
    asm volatile("mbarrier.arrive.expect_tx.shared::cta.b64 _, [%0], %1;" :: "r"(bar), "r"(bytes) : "memory");
}
__device__ __forceinline__ void mbar_arrive(uint32_t bar) { asm volatile("mbarrier.arrive.shared::cta.b64 _, [%0];" :: "r"(bar) : "memory"); }
__device__ __forceinline__ void mbar_arrive_cluster(uint32_t bar) { asm volatile("mbarrier.arrive.shared::cluster.b64 _, [%0];" :: "r"(bar) : "memory"); }
__device__ __forceinline__ bool mbar_try(uint32_t bar, uint32_t parity) {
    uint32_t ok;
    asm volatile("{\n.reg .pred p;\nmbarrier.try_wait.parity.shared::cta.b64 p, [%1], %2;\nselp.u32 %0, 1, 0, p;\n}\n" : "=r"(ok) : "r"(bar), "r"(parity) : "memory");
    return ok;
}
__device__ __forceinline__ bool mbar_test(uint32_t bar, uint32_t parity) {
    uint32_t ok;
    asm volatile("{\n.reg .pred p;\nmbarrier.test_wait.parity.shared::cta.b64 p, [%1], %2;\nselp.u32 %0, 1, 0, p;\n}\n" : "=r"(ok) : "r"(bar), "r"(parity) : "memory");
    return ok;
}
__device__ __forceinline__ void fail_if(bool c) { asm volatile("{\n.reg .pred p;\nsetp.ne.u32 p, %0, 0;\n@p st.volatile.global.u32 [%1], %0;\n}\n" :: "r"((uint32_t)c), "l"(0ull) : "memory"); }
__device__ __forceinline__ void mbar_wait(uint32_t bar, uint32_t parity) {
    int n = 0;
    while (!mbar_try(bar, parity)) fail_if(++n > (1 << 20));
}
__device__ __forceinline__ void st_async(uint32_t addr, uint32_t v, uint32_t bar) {
    asm volatile("st.async.weak.shared::cluster.mbarrier::complete_tx::bytes.u32 [%0], %1, [%2];" :: "r"(addr), "r"(v), "r"(bar) : "memory");
}
__device__ __forceinline__ uint32_t mapa(uint32_t a, uint32_t cta) { uint32_t d; asm("mapa.shared::cluster.u32 %0, %1, %2;" : "=r"(d) : "r"(a), "r"(cta)); return d; }
__device__ __forceinline__ uint32_t lds32(uint32_t a) { uint32_t v; asm volatile("ld.shared.b32 %0, [%1];" : "=r"(v) : "r"(a)); return v; }
__device__ __forceinline__ uint32_t lds32v(uint32_t a) { uint32_t v; asm volatile("ld.volatile.shared.b32 %0, [%1];" : "=r"(v) : "r"(a) : "memory"); return v; }
__device__ __forceinline__ void sts32(uint32_t a, uint32_t v) { asm volatile("st.shared.b32 [%0], %1;" :: "r"(a), "r"(v) : "memory"); }
__device__ __forceinline__ uint4 ldw(const uint4* a) { uint4 v; asm volatile("ld.weak.global.L1::no_allocate.v4.u32 {%0,%1,%2,%3}, [%4];" : "=r"(v.x), "=r"(v.y), "=r"(v.z), "=r"(v.w) : "l"(a) : "memory"); return v; }
__device__ __forceinline__ void mma_k8(float* c, uint2 a, uint32_t b) {
    asm volatile("mma.sync.aligned.m16n8k8.row.col.f32.bf16.bf16.f32 {%0,%1,%2,%3}, {%4,%5}, {%6}, {%0,%1,%2,%3};"
                 : "+f"(c[0]), "+f"(c[1]), "+f"(c[2]), "+f"(c[3]) : "r"(a.x), "r"(a.y), "r"(b));
}
__device__ __forceinline__ void mma_k16(float* d, uint2 a, uint2 a2, uint32_t b0, uint32_t b1, float c0, float c1, float c2, float c3) {
    asm volatile("mma.sync.aligned.m16n8k16.row.col.f32.bf16.bf16.f32 {%0,%1,%2,%3}, {%4,%5,%6,%7}, {%8,%9}, {%10,%11,%12,%13};"
                 : "=f"(d[0]), "=f"(d[1]), "=f"(d[2]), "=f"(d[3]) : "r"(a.x), "r"(a.y), "r"(a2.x), "r"(a2.y), "r"(b0), "r"(b1), "f"(c0), "f"(c1), "f"(c2), "f"(c3));
}
__device__ __forceinline__ uint32_t pack_bias(float lo, float hi, uint32_t bias2) {
    uint32_t p, o;
    asm("cvt.rn.bf16x2.f32 %0, %1, %2;" : "=r"(p) : "f"(hi), "f"(lo));
    asm("add.rn.bf16x2 %0, %1, %2;" : "=r"(o) : "r"(p), "r"(bias2));
    return o;
}

template <bool B> struct Flag { static constexpr bool value = B; };
struct Params {
    const uint16_t* w; const uint16_t* bias; const uint8_t* x;
    int nq, npages;
    int ncl, nh;
    int nctas;
    int tb, ta, te, slope0, slope1, c0;
    int m0;
    uint32_t ratio[8]; int rm[8];
};
struct Maps { CUtensorMap x[2], o[2], pf; };
__device__ __forceinline__ uint4 entry_w(int M, int w, int q, int extra) {
    const int r = M - (M >> 6), o = (r * 9363) >> 16, t = r - 7 * o, odd = t & 1, n = t >> 1;
    const int u = w ^ o ^ odd;
    const int C = 8 * o + 2 * n + ((n ^ u) & 1), C2 = 8 * o + 6 + ((1 ^ u) & 1);
    const uint32_t ra = 57 * C - ((C * 7282) >> 16) + 4 * odd, rb = odd ? 57 * C2 - ((C2 * 7282) >> 16) + 4 + 2 * n : ra + 12;
    const uint32_t rm = 2048 * (2 * (M >> 6) + w) + 56;
    const bool mixed = (M & 63) == 63;
    return make_uint4(M | (mixed << 14) | (q << 17) | (extra << 18), mixed ? rm * 0x10001u + (512u << 16) : ra * 0x10001u + (2u << 16),
                      mixed ? rm * 0x10001u + (1024u | 1536u << 16) : (ra + (odd ? 4 : 10)) | (rb << 16), 0);
}
__device__ __forceinline__ uint4 entry(int M, int q, int extra, unsigned long long plan) {
    const int r = M - (M >> 6), page = (r * 2341) >> 16;
    return entry_w(M, (M & 63) == 63 ? q : q ^ (int)((plan >> page) & 1), q, extra);
}
__device__ __forceinline__ int frontier(const Params& p, int t) {
    t = max(t, p.tb);
    const int l = t < p.ta ? LEAD0 + ((p.slope0 * (t - p.tb)) >> 16) : LEADE + max(0, (p.slope1 * (p.te - t)) >> 16);
    return (min(p.nq, t + l) * 9) >> 3;
}
__device__ __forceinline__ uint4 cl_entry(const Params& p, int m, int q, uint32_t ratio, unsigned long long plan) {
    const int nb = (m * ratio + 0x8000u) >> 16, nb1 = m ? ((m - 1) * ratio + 0x8000u) >> 16 : 0;
    uint4 e = entry(p.m0 + m + nb, q, nb - nb1, plan);
    const int c0 = frontier(p, p.m0 + m - 1 + nb1);
    e.w = c0 | (frontier(p, p.m0 + m + nb) - c0) << 16;
    return e;
}
__device__ __forceinline__ int helpers(const Params& p, unsigned long long plan, int q) {
    const int h0 = min(max(((p.ncl + p.nh) >> 1) - (p.ncl - (int)((plan >> 48) & 0xFF)), 0), p.nh);
    return q ? p.nh - h0 : h0;
}
__device__ __forceinline__ void draw(uint32_t& v, uint32_t* ctr, uint32_t inc) {
    asm volatile("{\n.reg .pred p;\nelect.sync _|p, 0xffffffff;\n@p atom.relaxed.gpu.global.add.u32 %0, [%1], %2;\n}" : "+r"(v) : "l"(ctr), "r"(inc) : "memory");
}
__device__ __forceinline__ uint4 lds128v(uint32_t a) { uint4 v; asm volatile("ld.volatile.shared.v4.b32 {%0,%1,%2,%3}, [%4];" : "=r"(v.x), "=r"(v.y), "=r"(v.z), "=r"(v.w) : "r"(a) : "memory"); return v; }
__device__ __forceinline__ void sts128(uint32_t a, uint4 e) { asm volatile("st.shared.v4.b32 [%0], {%1,%2,%3,%4};" :: "r"(a), "r"(e.x), "r"(e.y), "r"(e.z), "r"(e.w) : "memory"); }

__device__ __forceinline__ const uint8_t* probe_line(const Params& p, int page, int cell, int line, int parity) {
    return p.x + ((size_t)page << 21) + cell * 65536 + ((__popc(cell & 0xB) ^ parity) & 1) * 4096 + line * 128;
}
__device__ __forceinline__ int lag(const uint8_t* first, const uint8_t* second, uint32_t scratch, uint32_t since) {
    uint32_t t0, t1;
#pragma unroll 1
    for (int e = 0; e < 2; e++) {
        uint32_t a = 0, b = 0;
        asm volatile("{\n.reg .pred p;\nsetp.ne.s32 p, %4, 0;\n@p ld.global.cg.u32 %0, [%2];\n@p ld.global.cg.u32 %1, [%3];\n}"
                     : "+r"(a), "+r"(b) : "l"(first), "l"(second), "r"(e) : "memory");
        asm volatile("st.volatile.shared.u32 [%0], %1;" :: "r"(scratch), "r"(a) : "memory");
        asm volatile("mov.u32 %0, %%clock;" : "=r"(t0) :: "memory");
        asm volatile("st.volatile.shared.u32 [%0], %1;" :: "r"(scratch), "r"(b) : "memory");
        asm volatile("mov.u32 %0, %%clock;" : "=r"(t1) :: "memory");
        uint32_t t = t1;
        while (t - since < PWAIT) asm volatile("mov.u32 %0, %%clock;" : "=r"(t) :: "memory");
    }
    return t1 - t0;
}

template <bool HELPER>
__global__ void __launch_bounds__(NTHREADS, 1)
spgemm_kernel(const __grid_constant__ Params p, const __grid_constant__ Maps maps) {
    extern __shared__ unsigned char smem_raw[];
    const uint32_t sb = ((uint32_t)__cvta_generic_to_shared(smem_raw) + 1023u) & ~1023u;
    const int tid = threadIdx.x, warp = __shfl_sync(~0u, tid >> 5, 0), lane = tid & 31;
    const int rank = blockIdx.x % CL, cid = blockIdx.x / CL;
    const uint32_t bar_full = sb + OFF_FULL, bar_empty = sb + OFF_EMPTY, tk = sb + OFF_TK;
    const int pr = HELPER ? 2 : rank, pc = HELPER ? blockIdx.x : cid;
    const uint8_t* pl = probe_line(p, pr == 1 ? min(pc, p.npages - 1) : p.npages - 1, pr == 1 ? 30 : pc & 31,
                                   (pr == 1 ? 4 + 2 * max(pc + 1 - p.npages, 0) : pr * 15 + (pc >> 5) * 2) + (warp & 1), warp & 1);
    uint32_t tp;
    asm volatile("mov.u32 %0, %%clock;" : "=r"(tp) :: "memory");
    if (!HELPER && warp >= 14 && lane < 2) asm volatile("prefetch.global.L2 [%0];" :: "l"((const uint8_t*)((uintptr_t)pl ^ (lane << 12))) : "memory");
    uint4 wv[4];
    const int wrow = warp * 16 + (lane & 3) * 4;
    uint32_t b0, b1;
    auto prep_load = [&](int mtile) {
        b0 = __ldg(p.bias + mtile * 64 + lane); b1 = __ldg(p.bias + mtile * 64 + 32 + lane);
#pragma unroll
        for (int j = 0; j < 4; j++) wv[j] = __ldg((const uint4*)(p.w + (rank * 192 + wrow + j) * D + mtile * 64 + (lane >> 2) * 8));
    };
    if (!HELPER && warp < 12) {
        if (cid < 36) prep_load(cid >> 2);
        asm volatile("barrier.cluster.arrive.relaxed.aligned;" ::: "memory");
    }

    if (warp >= 12) {
        asm volatile("setmaxnreg.dec.sync.aligned.u32 32;");
        if (tid == NCONS) {
#pragma unroll
            for (int s = 0; s < NSLOT; s++) { mbar_init(bar_full + 8 * s, 1); mbar_init(bar_empty + 8 * s, HELPER ? 3 : 3 * CL); }
#pragma unroll
            for (int j = 0; j < 8; j++) sts32(tk + 16 * j, 0);
            mbar_init(sb + OFF_MBAR, 1); mbar_init(sb + OFF_MBAR + 8, 1);
            mbar_init(sb + OFF_GO, HELPER ? 12 : 12 + CL); mbar_init(sb + OFF_PLAN, 1); mbar_init(sb + OFF_PLAN2, 1);
            asm volatile("fence.mbarrier_init.release.cluster;" ::: "memory");
            mbar_expect_tx(sb + OFF_MBAR, 36 * 8);
            if (!HELPER && rank != 0) mbar_expect_tx(sb + OFF_PLAN, 16);
        }
        if (tid == NCONS + 32) {
            asm volatile("prefetch.tensormap [%0];" :: "l"(&maps.x[0]) : "memory");
            if (!HELPER) asm volatile("griddepcontrol.launch_dependents;");
            asm volatile("prefetch.tensormap [%0];" :: "l"(&maps.pf) : "memory");
            asm volatile("prefetch.tensormap [%0];" :: "l"(&maps.x[1]) : "memory");
#pragma unroll
            for (int j = 0; j < 2; j++) asm volatile("prefetch.tensormap [%0];" :: "l"(&maps.o[j]) : "memory");
        }
        __syncwarp();
        auto wait_plan = [&]() -> uint4 {
            unsigned long long a, b; int n = 0;
            do { asm volatile("ld.relaxed.gpu.global.v2.u64 {%0, %1}, [%2];" : "=l"(a), "=l"(b) : "l"(&g_plan) : "memory"); fail_if(++n > (1 << 22)); }
            while (__any_sync(~0u, (int)(a >> 56) + (int)(b >> 56) != 2 * p.ncl));
            b &= (1ull << 56) - 1;
            const int side = (b >> cid) & 1, n1 = __popcll(b), below = __popcll(b & ((1ull << cid) - 1));
            a = ((a ^ b) & ((1ull << 40) - 1)) | (unsigned long long)n1 << 48;
            return make_uint4((uint32_t)a, (uint32_t)(a >> 32), side | (side ? below : cid - below) << 8 | (side ? n1 : p.ncl - n1) << 16, 0);
        };
        auto measure = [&](uint32_t since) -> int {
            const int d = lag(pl, (const uint8_t*)((uintptr_t)pl ^ 4096), sb + OFF_INFO + 16 + 4 * (warp & 1), since);
            if (warp == 14 && lane == 0) sts32(sb + OFF_INFO + 24, d);
            asm volatile("bar.sync 11, 64;" ::: "memory");
            return d > (int)lds32v(sb + OFF_INFO + 24);
        };
        uint4 e0 = make_uint4(0, 0, 0, 0), e1 = e0;
        if (HELPER) {
            asm volatile("bar.sync 0;" ::: "memory");
            int side = 0;
            if (warp >= 14) side = measure(tp - PWAIT);
            if (warp == 15) {
                uint32_t old = 0;
                if (lane == 0) {
                    old = atomicAdd(&g_hreg[rank * 32], side ? 0x10000u : 1u);
                    if ((old & 0xFFFF) + (old >> 16) == p.nh - 1) g_hreg[rank * 32] = 0;
                }
                const uint4 inf = wait_plan();
                const unsigned long long plan = inf.x | ((unsigned long long)inf.y << 32);
                old = __shfl_sync(~0u, old, 0);
                int idx = side ? p.nh - 1 - (old >> 16) : old & 0xFFFF, nh = helpers(p, plan, 0), q = 0;
                if (idx >= nh) { idx -= nh; nh = p.nh - nh; q ^= 1; }
                const uint32_t ratio = p.ratio[nh];
                const int rm = p.rm[nh], H = p.nq - p.m0 - rm;
                for (int j0 = 0; __any_sync(~0u, idx + (j0 - 1) * nh < H); j0 += 32) {
                    const int k = idx + (j0 + lane) * nh, mk = (((k + 1) << 16) - 0x8000u + ratio - 1) / ratio;
                    uint4 e = entry(p.m0 + min(mk, rm) + k, q, 0, plan);
                    if (k >= H) e.x = NO_TILE;
                    sts128(sb + OFF_TAB + 16 * (j0 + lane), e);
                }
                __syncwarp();
                if (lane == 0) mbar_arrive(sb + OFF_PLAN);
            }
        } else {
            asm volatile("barrier.cluster.arrive.relaxed.aligned;" ::: "memory");
            if (warp == 12) { e0 = entry_w(cid, 0, 0, 0); e1 = entry_w(cid, 1, 1, 0); }
            if (rank < 2 && warp >= 14) {
                const int side = measure(tp);
                if (warp == 15 && lane == 0) asm volatile("red.relaxed.gpu.global.add.u64 [%0], %1;" :: "l"(rank ? &g_plan.x : &g_plan.y), "l"((1ull << 56) | (unsigned long long)side << cid) : "memory");
            }
            asm volatile("barrier.cluster.wait.aligned;" ::: "memory");
            if (warp >= 13) {
                if (warp == 15 && rank == 0) {
                    const uint4 inf = wait_plan();
                    if (lane == 0) sts128(sb + OFF_INFO, inf);
                    else if (lane < CL)
                        asm volatile("st.async.weak.shared::cluster.mbarrier::complete_tx::bytes.v4.u32 [%0], {%1, %2, %3, %4}, [%5];"
                                     :: "r"(mapa(sb + OFF_INFO, lane)), "r"(inf.x), "r"(inf.y), "r"(inf.z), "r"(inf.w), "r"(mapa(sb + OFF_PLAN, lane)) : "memory");
                }
                if (rank == 0) asm volatile("bar.sync 15, 96;" ::: "memory"); else mbar_wait(sb + OFF_PLAN, 0);
                const uint4 inf = lds128v(sb + OFF_INFO);
                const unsigned long long plan = inf.x | ((unsigned long long)inf.y << 32);
                const int nh = helpers(p, plan, inf.z & 1), rm = p.rm[nh], nc = inf.z >> 16;
                const uint32_t ratio = p.ratio[nh];
                if (warp == 15 && rank == 0) {
                    const int m = ((inf.z >> 8) & 0xFF) + min(lane, NSTAT - 1) * nc;
                    sts128(sb + OFF_TAB + 16 * m, cl_entry(p, m, inf.z & 1, ratio, plan));
                    __syncwarp();
                    if (lane == 0) { mbar_arrive(sb + OFF_PLAN); mbar_expect_tx(sb + OFF_PLAN2, 16 * (rm - NSTAT * nc)); }
                }
                const uint32_t rtab = mapa(sb + OFF_TAB, 0), rbar = mapa(sb + OFF_PLAN2, 0);
                for (int m0 = NSTAT * nc + 96 * (2 - rank); __any_sync(~0u, m0 < rm); m0 += 288) {
                    const int m = m0 + tid - (NCONS + 32);
                    const uint4 e = cl_entry(p, m, inf.z & 1, ratio, plan);
                    if (m < rm) asm volatile("st.async.weak.shared::cluster.mbarrier::complete_tx::bytes.v4.u32 [%0], {%1, %2, %3, %4}, [%5];"
                                             :: "r"(rtab + 16 * m), "r"(e.x), "r"(e.y), "r"(e.z), "r"(e.w), "r"(rbar) : "memory");
                }
            }
        }
        if (warp == 12) {
            if (!HELPER && rank != 0) {
                mbar_wait(sb + OFF_PLAN, 0);
                const uint4 inf = lds128v(sb + OFF_INFO);
                const unsigned long long plan = inf.x | ((unsigned long long)inf.y << 32);
                auto cell = [&](int c, int q) {
                    const int y = 32 * c - 2 + 4 * ((__popc(c & 0xB) ^ (int)(plan >> (c >> 5)) ^ q) & 1);
                    asm volatile("{\n.reg .pred p;\nelect.sync _|p, 0xffffffff;\n@p cp.async.bulk.prefetch.tensor.3d.L2.global.tile [%0, {%1, %2, %1}];\n}" :: "l"(&maps.pf), "r"(0), "r"(y) : "memory");
                };
                const int fe0 = frontier(p, 0), step = 2 * (inf.z >> 16);
                int u0 = p.c0 + 2 * ((inf.z >> 8) & 0xFF) + rank - 1;
                {
                    uint32_t t, due;
                    asm volatile("mov.u32 %0, %%clock;" : "=r"(due) :: "memory");
                    due += (PACE * (u0 - p.c0)) / step;
                    for (; __any_sync(~0u, u0 < fe0); u0 += step, due += PACE) {
                        do { asm volatile("mov.u32 %0, %%clock;" : "=r"(t) :: "memory"); } while (__any_sync(~0u, (int)(t - due) < 0));
                        cell(u0, inf.z & 1);
                    }
                }
                for (int j = XEARLY + rank - 1;; j += 2) {
                    uint4 v; uint32_t ahead;
                    for (int n = 0; __any_sync(~0u, (ahead = (((v = lds128v(tk + ((j & 7) << 4))).x >> 20) - (j + 1)) & 0xFFF) >= 0x800); n++) {
                        if (__any_sync(~0u, lds32v(tk + (((j - 1) & 7) << 4)) == (NO_TILE | (uint32_t)j << 20))) { v.x = NO_TILE; break; }
                        __nanosleep(100); fail_if(n > (1 << 24));
                    }
                    if (__any_sync(~0u, (v.x & NO_TILE) == NO_TILE)) break;
                    j += __reduce_max_sync(~0u, ahead);
                    for (int u = v.w & 0xFFFF; __any_sync(~0u, u < (v.w & 0xFFFF) + (v.w >> 16)); u++) cell(u, (v.x >> 17) & 1);
                }
            } else {
                const uint32_t rtk = HELPER ? tk : mapa(tk, lane < CL ? lane : 0), rfull = HELPER ? bar_full : mapa(bar_full, lane < CL ? lane : 0);
                int s = 0; uint32_t ph = 1;
                uint64_t pol;
                if (!HELPER) asm volatile("createpolicy.fractional.L2::evict_first.b64 %0, 1.0;" : "=l"(pol));
                else asm volatile("createpolicy.fractional.L2::evict_normal.b64 %0, 1.0;" : "=l"(pol));
                auto request = [&](int j, const uint4& t) {
                    const bool valid = t.x != NO_TILE;
                    const CUtensorMap* tm = &maps.x[(t.x >> 14) & 1];
                    mbar_wait(bar_empty + 8 * s, ph);
                    if (__any_sync(~0u, valid)) {
                        const uint32_t dst = sb + OFF_X + s * TILE_BYTES;
                        if (HELPER)
                            asm volatile("{\n.reg .pred p;\nelect.sync _|p, 0xffffffff;\n"
                                         "@p cp.async.bulk.tensor.4d.shared::cluster.global.mbarrier::complete_tx::bytes.L2::cache_hint [%0], [%4, {%6, %7, %6, %6}], [%5], %11;\n"
                                         "@p cp.async.bulk.tensor.4d.shared::cluster.global.mbarrier::complete_tx::bytes.L2::cache_hint [%1], [%4, {%6, %8, %6, %6}], [%5], %11;\n"
                                         "@p cp.async.bulk.tensor.4d.shared::cluster.global.mbarrier::complete_tx::bytes.L2::cache_hint [%2], [%4, {%6, %9, %6, %6}], [%5], %11;\n"
                                         "@p cp.async.bulk.tensor.4d.shared::cluster.global.mbarrier::complete_tx::bytes.L2::cache_hint [%3], [%4, {%6, %10, %6, %6}], [%5], %11;\n}\n"
                                         :: "r"(dst), "r"(dst + 9216), "r"(dst + 2 * 9216), "r"(dst + 3 * 9216), "l"(tm), "r"(bar_full + 8 * s), "r"(0),
                                            "r"(t.y & 0xFFFF), "r"(t.y >> 16), "r"(t.z & 0xFFFF), "r"(t.z >> 16), "l"(pol) : "memory");
                        else
                            asm volatile("{\n.reg .pred p;\nelect.sync _|p, 0xffffffff;\n"
                                         "@p cp.async.bulk.tensor.4d.shared::cluster.global.mbarrier::complete_tx::bytes.multicast::cluster.L2::cache_hint [%0], [%4, {%6, %7, %6, %6}], [%5], %11, %12;\n"
                                         "@p cp.async.bulk.tensor.4d.shared::cluster.global.mbarrier::complete_tx::bytes.multicast::cluster.L2::cache_hint [%1], [%4, {%6, %8, %6, %6}], [%5], %11, %12;\n"
                                         "@p cp.async.bulk.tensor.4d.shared::cluster.global.mbarrier::complete_tx::bytes.multicast::cluster.L2::cache_hint [%2], [%4, {%6, %9, %6, %6}], [%5], %11, %12;\n"
                                         "@p cp.async.bulk.tensor.4d.shared::cluster.global.mbarrier::complete_tx::bytes.multicast::cluster.L2::cache_hint [%3], [%4, {%6, %10, %6, %6}], [%5], %11, %12;\n}\n"
                                         :: "r"(dst), "r"(dst + 9216), "r"(dst + 2 * 9216), "r"(dst + 3 * 9216), "l"(tm), "r"(bar_full + 8 * s), "r"(0),
                                            "r"(t.y & 0xFFFF), "r"(t.y >> 16), "r"(t.z & 0xFFFF), "r"(t.z >> 16), "h"((uint16_t)((1u << CL) - 1)), "l"(pol) : "memory");
                    }
                    if (HELPER) {
                        if (lane == 0) { sts128(tk + ((j & 7) << 4), t); mbar_expect_tx(bar_full + 8 * s, valid ? TILE_BYTES : 0); }
                    } else if (lane < CL) {
                        asm volatile("mbarrier.arrive.expect_tx.shared::cluster.b64 _, [%0], %1;" :: "r"(rfull + 8 * s), "r"(valid ? TILE_BYTES + 16 : 16) : "memory");
                        asm volatile("st.async.weak.shared::cluster.mbarrier::complete_tx::bytes.v4.u32 [%0], {%1, %2, %3, %4}, [%5];"
                                     :: "r"(rtk + ((j & 7) << 4)), "r"(t.x | ((uint32_t)(j + 1) << 20)), "r"(t.y), "r"(t.z), "r"(t.w), "r"(rfull + 8 * s) : "memory");
                    }
                    if (++s == NSLOT) { s = 0; ph ^= 1; }
                };
                if (HELPER) {
#pragma unroll 1
                    for (int j = 0; j < XEARLY; j++) request(j, entry_w(p.ncl + cid + (j >> 1) * (p.ncl + p.nh), j & 1, j & 1, 0));
                    mbar_wait(sb + OFF_PLAN, 0);
                    mbar_wait(sb + OFF_GO, 0);
                    for (int j = XEARLY;; j++) {
                        const uint4 t = lds128v(sb + OFF_TAB + 16 * (j - XEARLY));
                        request(j, t);
                        if (__any_sync(~0u, t.x == NO_TILE)) break;
                    }
                } else {
                    static_assert(XEARLY == 2, "");
                    request(0, e0);
                    request(1, e1);
                    mbar_wait(sb + OFF_PLAN, 0);
                    const uint4 inf = lds128v(sb + OFF_INFO);
                    const unsigned long long plan = inf.x | ((unsigned long long)inf.y << 32);
                    const int side = inf.z & 1, nc = inf.z >> 16;
                    const int nh = helpers(p, plan, side), rm = p.rm[nh], rmo = p.rm[p.nh - nh];
                    const uint32_t ratio = p.ratio[nh], ratioo = p.ratio[p.nh - nh];
                    const int st = NSTAT * nc, sto = NSTAT * (p.ncl - nc);
                    uint4 t = lds128v(sb + OFF_TAB + 16 * ((inf.z >> 8) & 0xFF));
                    mbar_wait(sb + OFF_GO, 0);
                    int j = XEARLY;
#pragma unroll 1
                    for (; j < XEARLY + NSTAT - 2; j++) {
                        const uint4 tn = lds128v(sb + OFF_TAB + 16 * (((inf.z >> 8) & 0xFF) + (j + 1 - XEARLY) * nc));
                        request(j, t);
                        t = tn;
                    }
                    uint32_t drawn = 0;
                    int q = side;
                    request(j++, t);
                    draw(drawn, &g_ticket, 1u << (16 * side));
                    t = lds128v(sb + OFF_TAB + 16 * (((inf.z >> 8) & 0xFF) + (NSTAT - 1) * nc));
                    mbar_wait(sb + OFF_PLAN2, 0);
                    for (;; j++) {
                        request(j, t);
                        uint32_t v = __reduce_max_sync(~0u, drawn);
                        int m = st + ((v >> (16 * side)) & 0xFFFF), mo = sto + ((v >> (16 - 16 * side)) & 0xFFFF);
                        if (q == side ? m >= rm && mo < rmo : mo >= rmo && m < rm) {
                            q ^= 1;
                            draw(drawn, &g_ticket, 1u << (16 * q));
                            v = __reduce_max_sync(~0u, drawn);
                            m = st + ((v >> (16 * side)) & 0xFFFF); mo = sto + ((v >> (16 - 16 * side)) & 0xFFFF);
                        }
                        if (q == side ? m >= rm : mo >= rmo) break;
                        const bool own = q == side;
                        q = m + ((m * ratio) >> 16) > mo + ((mo * ratioo) >> 16) + DELTA ? side ^ 1 : side;
                        draw(drawn, &g_ticket, 1u << (16 * q));
                        if (own) t = lds128v(sb + OFF_TAB + 16 * m);
                        else t = cl_entry(p, mo, side ^ 1, ratioo, plan);
                    }
                    t.x = NO_TILE;
                    request(j + 1, t);
                    if (lane == 0 && atomicInc(&g_done, p.ncl - 1) == (uint32_t)p.ncl - 1) g_ticket = 0;
                }
            }
        } else {
            const int g = warp - 13;
            uint64_t spol;
            asm volatile("createpolicy.fractional.L2::evict_first.b64 %0, 1.0;" : "=l"(spol));
            mbar_wait(sb + OFF_GO, 0);
            if (g == 2 && lane == 0 && atomicInc(&g_passed, p.nctas - 1) == (uint32_t)p.nctas - 1) {
#pragma unroll
                for (int m = 0; m < 36; m++) g_ready[m * 32] = 0;
                g_plan = make_ulonglong2(0, 0);
            }
            __syncwarp();
            for (int i = 0;; i++) {
                asm volatile("bar.arrive %0, 160;" :: "r"(12 + g) : "memory");
                asm volatile("bar.sync %0, 160;" :: "r"(1 + g) : "memory");
                const uint4 t = lds128v(tk + ((i & 7) << 4));
                if ((t.x & NO_TILE) == NO_TILE) break;
                const CUtensorMap* tm = &maps.o[(t.x >> 14) & 1];
                const int row[4] = {(int)(t.y & 0xFFFF), (int)(t.y >> 16), (int)(t.z & 0xFFFF), (int)(t.z >> 16)};
                if (lane == 0) {
#pragma unroll
                    for (int k = 0; k < 4; k++)
                        asm volatile("cp.async.bulk.tensor.3d.global.shared::cta.bulk_group.L2::cache_hint [%0, {%2, %3, %4}], [%1], %5;"
                                     :: "l"(tm), "r"(sb + OFF_STG + g * STG_BYTES + k * 1024), "r"((g * 3 + rank) * 64), "r"(row[k]), "r"(0), "l"(spol) : "memory");
                    asm volatile("cp.async.bulk.commit_group;" ::: "memory");
                    asm volatile("cp.async.bulk.wait_group.read 0;" ::: "memory");
                }
                __syncwarp();
            }
        }
        __syncwarp();
        if (!HELPER) asm volatile("barrier.cluster.arrive.relaxed.aligned;\nbarrier.cluster.wait.aligned;" ::: "memory");
    } else {
        asm volatile("setmaxnreg.inc.sync.aligned.u32 160;");
        const int wg = warp >> 2, wtid = tid & 127;
        if (HELPER) asm volatile("bar.sync 0;" ::: "memory");
        else {
            int prb = cid;
            if (prb >= 36) asm volatile("barrier.cluster.wait.aligned;" ::: "memory");
#pragma unroll 1
            for (int round = 0; prb < 36; prb += p.ncl, round++) {
                const uint32_t wsm = sb + OFF_WST, msk = sb + OFF_MSK + (round & 1) * 288, mbar = sb + OFF_MBAR + (round & 1) * 8;
                if (round) {
                    asm volatile("bar.sync 3, 384;" ::: "memory");
                    if (tid == 0) mbar_expect_tx(mbar, 36 * 8);
                    prep_load(prb >> 2);
                }
                const int nt = ties(wv[0].x, wv[1].x, wv[2].x, wv[3].x) + ties(wv[0].y, wv[1].y, wv[2].y, wv[3].y) +
                               ties(wv[0].z, wv[1].z, wv[2].z, wv[3].z) + ties(wv[0].w, wv[1].w, wv[2].w, wv[3].w);
                const uint32_t mk = __ballot_sync(~0u, nt > 0), md = __ballot_sync(~0u, nt > 1);
                if (round == 0) asm volatile("barrier.cluster.wait.aligned;" ::: "memory");
                if (lane < CL)
                    asm volatile("st.async.weak.shared::cluster.mbarrier::complete_tx::bytes.v2.u32 [%0], {%1, %2}, [%3];"
                                 :: "r"(mapa(msk + (rank * 12 + warp) * 8, lane)), "r"(mk), "r"(md), "r"(mapa(mbar, lane)) : "memory");
#pragma unroll
                for (int j = 0; j < 4; j++) {
                    const int row = wrow + j;
                    const uint32_t ad = wsm + row * 128 + (((lane >> 2) ^ ((row & 1) | ((row >> 1) & 6))) << 4);
                    asm volatile("st.shared.v4.b32 [%0], {%1,%2,%3,%4};" :: "r"(ad), "r"(wv[j].x), "r"(wv[j].y), "r"(wv[j].z), "r"(wv[j].w) : "memory");
                }
                if (warp == 0) {
                    mbar_wait(mbar, (round >> 1) & 1);
                    uint4 ms = make_uint4(0, 0, 0, 0);
                    if (lane < KSTEPS) ms = lds128v(msk + 16 * lane);
                    const uint32_t te = (ms.x & 0x0F0F0F0Fu) | ((ms.z & 0x0F0F0F0Fu) << 4), to = ((ms.x >> 4) & 0x0F0F0F0Fu) | (ms.z & 0xF0F0F0F0u);
                    const uint32_t de = (ms.y & 0x0F0F0F0Fu) | ((ms.w & 0x0F0F0F0Fu) << 4), dq = ((ms.y >> 4) & 0x0F0F0F0Fu) | (ms.w & 0xF0F0F0F0u);
                    auto count = [](uint32_t v) { v -= (v >> 1) & 0x55555555u; v = (v & 0x33333333u) + ((v >> 2) & 0x33333333u); return (v + (v >> 4)) & 0x0F0F0F0Fu; };
                    const uint32_t c0 = __reduce_add_sync(~0u, count(te)), c1 = __reduce_add_sync(~0u, count(to));
                    auto byte = [](uint32_t a, uint32_t b, uint32_t u) { return __byte_perm(a, b, (u >> 1) + 4 * (u & 1)) & 0xFFu; };
                    const uint32_t ku = byte(c0, c1, lane & 7) * 8 + (lane & 7), k2 = 2 * (lane >> 3);
                    const uint32_t ranks = __reduce_add_sync(~0u, ((byte(c0, c1, k2) * 8 + k2 < ku) + (byte(c0, c1, k2 + 1) * 8 + k2 + 1 < ku)) << (4 * (lane & 7)));
                    const uint32_t order = __reduce_add_sync(~0u, lane < 8 ? lane << (4 * ((ranks >> (4 * lane)) & 7)) : 0);
                    int cnt[4]; uint32_t mq = 0;
#pragma unroll
                    for (int z = 0; z < 4; z++) {
                        const uint32_t ua = (order >> (4 * z)) & 7, ub = (order >> (28 - 4 * z)) & 7;
                        const uint32_t ta = byte(te, to, ua), tb = byte(te, to, ub), v = ta | tb | ((ta & tb) | byte(de, dq, ua) | byte(de, dq, ub)) << 8;
                        cnt[z] = __popc(v);
                        if (z == (prb & 3)) mq = v;
                    }
                    const uint32_t l01 = __reduce_add_sync(~0u, cnt[0] | cnt[1] << 16), l23 = __reduce_add_sync(~0u, cnt[2] | cnt[3] << 16);
                    const int ulo = (order >> (4 * (prb & 3))) & 7, uhi = (order >> (28 - 4 * (prb & 3))) & 7;
                    const int full = max(max(max((int)(l01 & 0xFFFF) - cnt[0], (int)(l01 >> 16) - cnt[1]), max((int)(l23 & 0xFFFF) - cnt[2], (int)(l23 >> 16) - cnt[3])), 16);
                    const int twice = __reduce_min_sync(~0u, lane < KSTEPS ? full << 12 | (65 - cnt[0] - cnt[1] - cnt[2] - cnt[3]) << 5 | lane : full << 12 | 31) & 31;
                    sts32(sb + OFF_SEL + 4 * lane, lane == 31 ? ulo | (uhi << 4) | (twice << 8) : lane == twice ? 0 : mq);
                }
                asm volatile("bar.sync 1, 384;" ::: "memory");
                const uint32_t units = lds32v(sb + OFF_SEL + 4 * 31), mq = lds32v(sb + OFF_SEL + 4 * min(lane, 30));
                uint32_t wm[4];
                load_units(wsm, warp, units & 7, (units >> 4) & 7, lane, wm);
                emit_half(wm, mq, prb, rank * 6 + (warp >> 1), warp & 1, lane, units, b0, b1);
                asm volatile("bar.sync 2, 384;" ::: "memory");
                if (tid == 0) asm volatile("red.release.gpu.global.add.u32 [%0], 1;" :: "l"(&g_ready[prb * 32]) : "memory");
            }
            if (warp == 0 && lane < CL) mbar_arrive_cluster(mapa(sb + OFF_GO, lane));
        }
        const int mt = wg * 3 + rank, rb = mt * 4 + (warp & 3);
        {
            uint32_t v; int n = 0;
            do { asm volatile("ld.acquire.gpu.global.u32 %0, [%1];" : "=r"(v) : "l"(&g_ready[rb * 32]) : "memory"); fail_if(++n > (1 << 22)); } while (__any_sync(~0u, v < CL));
        }
        if (wg > 0) asm volatile("bar.sync %0, 256;" :: "r"(7 + wg) : "memory");
        uint32_t a[KSTEPS + 1][4], meta[9];
        uint2 rv[3]; uint32_t ro[3], sel[3];
        uint32_t info, bias_lo, bias_hi;
        {
            const uint4* ap = g_aux + rb * 6 * 32 + lane;
            const uint4 v3 = ldw(ap + 96), v2 = ldw(ap + 64), v4 = ldw(ap + 128), v5 = ldw(ap + 160), v0 = ldw(ap), v1 = ldw(ap + 32);
            meta[0] = v0.x; meta[1] = v0.y; meta[2] = v0.z; meta[3] = v0.w; meta[4] = v1.x; meta[5] = v1.y; meta[6] = v1.z; meta[7] = v1.w;
            meta[8] = v2.x; info = v2.y; bias_lo = v2.z; bias_hi = v2.w;
            ro[0] = v3.x; ro[1] = v3.y; ro[2] = v3.z;
            rv[0] = make_uint2(v4.x, v4.y); rv[1] = make_uint2(v4.z, v4.w); rv[2] = make_uint2(v5.x, v5.y);
        }
#pragma unroll
        for (int k = 0; k < KSTEPS + 1; k++) { uint4 v = ldw(&g_afrag[(mt * (KSTEPS + 1) + k) * 128 + wtid]); a[k][0] = v.x; a[k][1] = v.y; a[k][2] = v.z; a[k][3] = v.w; }
        if (wg < 2) asm volatile("bar.arrive %0, 256;" :: "r"(8 + wg) : "memory");
        if (lane == 0) mbar_arrive(sb + OFF_GO);
        auto selector = [](uint32_t o) { return 0x5410u + ((o >> 15) & 1) * 0x22u + (o >> 31) * 0x2200u; };
#pragma unroll
        for (int j = 0; j < 3; j++) { sel[j] = selector(ro[j]); ro[j] &= 0x7FFF7FFFu; }
        mbar_wait(bar_full, 0);
        info = __shfl_sync(~0u, info, 0);
        const int ngrp = info & 0xFF, ulo = (info >> 8) & 7, uhi = (info >> 12) & 7;
        const uint32_t stg = sb + OFF_STG + wg * STG_BYTES + ((lane >> 4) * 8 + (lane & 7)) * 128 + (((((lane >> 3) & 1) ? uhi : ulo) ^ (lane & 7)) << 4);
        const uint32_t twice = (((info >> 17) & 15) * 1024 + ((info >> 16) & 1) * 64) >> 4;
        const uint32_t rempty = HELPER ? bar_empty : mapa(bar_empty, 0);
        float acc[NACC];
        uint32_t bq[NB][6];
        auto gather = [&](uint32_t xb) {
#pragma unroll
            for (int j = 0; j < 4; j++) {
                const uint32_t o = xb + ((j & 1) ? ro[j >> 1] >> 16 : ro[j >> 1] & 0xFFFF);
#pragma unroll
                for (int n = 0; n < NB; n++) {
                    bq[n][j] = 0;
                    asm volatile("{\n.reg .pred p;\nsetp.lt.s32 p, %2, %3;\n@p ld.shared.b32 %0, [%1];\n}" : "+r"(bq[n][j]) : "r"(o + n * 9216), "r"(j), "r"(ngrp) : "memory");
                }
            }
        };
        auto select = [&]() {
#pragma unroll
            for (int n = 0; n < NB; n++)
#pragma unroll
                for (int j = 0; j < 2; j++) bq[n][2 * j] = __byte_perm(bq[n][2 * j], bq[n][2 * j + 1], sel[j]);
        };
        auto further = [&](uint32_t xb, int bar) {
#pragma unroll 1
            for (int y = 4; y < min(ngrp, 5); y++) {
#pragma unroll
                for (int n = 0; n < NB; n++) { bq[n][4] = lds32(xb + (ro[2] & 0xFFFF) + n * 9216); bq[n][5] = lds32(xb + (ro[2] >> 16) + n * 9216); }
#pragma unroll
                for (int n = 0; n < NB; n++) mma_k8(acc + 4 * n, rv[2], __byte_perm(bq[n][4], bq[n][5], sel[2]));
                if (bar >= 0) asm volatile("bar.arrive %0, 256;" :: "r"(bar) : "memory");
#pragma unroll 1
                for (int z = 3; 2 * z < ngrp; z++) {
                    const uint2 v = __ldca(&g_rval[(rb * 36 + z) * 32 + lane]); const uint32_t off = __ldca(&g_roff[(rb * 36 + z) * 32 + lane]);
                    uint32_t bx[NB];
#pragma unroll
                    for (int n = 0; n < NB; n++) bx[n] = __byte_perm(lds32(xb + (off & 0x7FFF) + n * 9216), lds32(xb + ((off >> 16) & 0x7FFF) + n * 9216), selector(off));
#pragma unroll
                    for (int n = 0; n < NB; n++) mma_k8(acc + 4 * n, v, bx[n]);
                }
            }
        };
        bool more = true;
#pragma unroll
        for (int n = 0; n < NB; n++) bq[n][4] = bq[n][5] = 0;
        gather(sb + OFF_X);
        select();
#pragma unroll
        for (int n = 0; n < NB; n++) mma_k16(acc + 4 * n, rv[0], rv[1], bq[n][0], bq[n][2], 0.f, 0.f, 0.f, 0.f);
        further(sb + OFF_X, -1);
        const int bar_a = 8 + wg, bar_an = 8 + (wg + 2) % 3, bar_tn = 4 + (wg + 2) % 3;
        if (wg == 1) asm volatile("bar.arrive 4, 256;" ::: "memory");
        if (wg == 2) { asm volatile("bar.sync 10, 256;" ::: "memory"); asm volatile("bar.arrive 5, 256;" ::: "memory"); }
        auto run = [&](auto tw) {
        constexpr bool TW = decltype(tw)::value;
        int s = 0; uint32_t ph = 0;
        bool ready = false;
        for (int i = 0; more; i++) {
            const uint32_t xb = sb + OFF_X + s * TILE_BYTES;
            const int s1 = s + 1 == NSLOT ? 0 : s + 1;
            const uint32_t ph1 = s1 == 0 ? ph ^ 1 : ph;
            asm volatile("bar.sync %0, 256;" :: "r"(4 + wg) : "memory");
            const uint64_t desc = ((uint64_t)1 << 62) | ((uint64_t)(9216 >> 4) << 32) | ((uint64_t)1 << 16) | (uint64_t)(xb >> 4);
            asm volatile("wgmma.fence.sync.aligned;" ::: "memory");
#pragma unroll
            for (int k = 0; k < KSTEPS; k++) {
                const uint64_t d = desc + (uint64_t)(((k >> 1) * 1024 + (k & 1) * 64) >> 4);
                if (k & 1) wgmma_sp<1>(acc, a[k], d, meta[k >> 1]);
                else       wgmma_sp<0>(acc, a[k], d, meta[k >> 1]);
            }
            if (TW) wgmma_sp<0>(acc, a[KSTEPS], desc + twice, 0x44444444u);
            asm volatile("wgmma.commit_group.sync.aligned;" ::: "memory");
            asm volatile("bar.arrive %0, 256;" :: "r"(bar_an) : "memory");
            if (!ready) mbar_wait(bar_full + 8 * s1, ph1);
            const uint32_t tn = lds32v(tk + (((i + 1) & 7) << 4));
            gather(sb + OFF_X + s1 * TILE_BYTES);
            asm volatile("bar.sync %0, 160;" :: "r"(12 + wg) : "memory");
            asm volatile("wgmma.wait_group.sync.aligned 0;" ::: "memory");
            if (wtid == 0) { if (HELPER) mbar_arrive(bar_empty + 8 * s); else mbar_arrive_cluster(rempty + 8 * s); }
#pragma unroll
            for (int n = 0; n < NB; n += 2) {
                const uint32_t p0 = pack_bias(acc[4 * n], acc[4 * n + 1], bias_lo), p1 = pack_bias(acc[4 * n + 2], acc[4 * n + 3], bias_hi);
                const uint32_t p2 = pack_bias(acc[4 * n + 4], acc[4 * n + 5], bias_lo), p3 = pack_bias(acc[4 * n + 6], acc[4 * n + 7], bias_hi);
                if (n == 0) asm volatile("stmatrix.sync.aligned.m8n8.x4.trans.shared.b16 [%0], {%1,%2,%3,%4};" :: "r"(stg + n * 1024), "r"(p0), "r"(p1), "r"(p2), "r"(p3) : "memory");
                else asm volatile("{\n.reg .pred p;\nAGAIN:\nstmatrix.sync.aligned.m8n8.x4.trans.shared.b16 [%0], {%1,%2,%3,%4};\nsetp.eq.u32 p, %5, 0xFFFFFFFE;\n@p bra.uni AGAIN;\n}"
                                  :: "r"(stg + n * 1024), "r"(p0), "r"(p1), "r"(p2), "r"(p3), "r"(info) : "memory");
            }
            more = __any_sync(~0u, (tn & NO_TILE) != NO_TILE);
            select();
            if (wg != 2 || more) {
                asm volatile("{\n.reg .pred p;\nTURN:\nbar.sync %0, 256;\nsetp.eq.u32 p, %1, 0xFFFFFFFF;\n@p bra.uni TURN;\n}" :: "r"(bar_a), "r"(info) : "memory");
#pragma unroll
                for (int n = 0; n < NB; n++) {
                    mma_k16(acc + 4 * n, rv[0], rv[1], bq[n][0], bq[n][2], 0.f, 0.f, 0.f, 0.f);
                    if (n == 0) asm volatile("{\n.reg .pred p;\nsetp.le.s32 p, %1, 4;\n@p bar.arrive %0, 256;\n}" :: "r"(bar_tn), "r"(ngrp) : "memory");
                }
                further(sb + OFF_X + s1 * TILE_BYTES, bar_tn);
            }
            asm volatile("fence.proxy.async.shared::cta;" ::: "memory");
            asm volatile("bar.arrive %0, 160;" :: "r"(1 + wg) : "memory");
            s = s1; ph = ph1;
            ready = __all_sync(~0u, mbar_test(bar_full + 8 * (s + 1 == NSLOT ? 0 : s + 1), s + 1 == NSLOT ? ph ^ 1 : ph));
        }
        };
        if (((info >> 16) & 31) < KSTEPS) run(Flag<true>()); else run(Flag<false>());
        if (wg == 0) asm volatile("bar.sync 4, 256;" ::: "memory");
        asm volatile("bar.sync %0, 160;" :: "r"(12 + wg) : "memory");
        asm volatile("bar.arrive %0, 160;" :: "r"(1 + wg) : "memory");
        if (!HELPER) asm volatile("barrier.cluster.arrive.relaxed.aligned;\nbarrier.cluster.wait.aligned;" ::: "memory");
    }
}

typedef CUresult (*EncodeFn)(CUtensorMap*, CUtensorMapDataType, cuuint32_t, void*, const cuuint64_t*, const cuuint64_t*, const cuuint32_t*, const cuuint32_t*,
                             CUtensorMapInterleave, CUtensorMapSwizzle, CUtensorMapL2promotion, CUtensorMapFloatOOBfill);

__global__ void plain_kernel(const __nv_bfloat16* x, const __nv_bfloat16* w, const __nv_bfloat16* b, __nv_bfloat16* out, int ntok) {
    const int t0 = blockIdx.x * 8;
    for (int f = threadIdx.x; f < D; f += blockDim.x) {
        float acc[8] = {};
        for (int g = 0; g < D / 4; g++) {
            float v[4], m[4];
            for (int i = 0; i < 4; i++) { v[i] = __bfloat162float(w[(4 * g + i) * D + f]); m[i] = fabsf(v[i]); }
            const float thr = fmaxf(fminf(fmaxf(m[0], m[1]), fmaxf(m[2], m[3])), fmaxf(fminf(m[0], m[1]), fminf(m[2], m[3])));
            for (int i = 0; i < 4; i++)
                for (int t = 0; t < 8; t++)
                    if (m[i] >= thr && t0 + t < ntok) acc[t] += v[i] * __bfloat162float(x[(size_t)(t0 + t) * D + 4 * g + i]);
        }
        for (int t = 0; t < 8; t++)
            if (t0 + t < ntok) out[(size_t)(t0 + t) * D + f] = __hadd(__float2bfloat16(acc[t]), b[f]);
    }
}

extern "C" void kernel_launch(void* const* d_in, const int* in_sizes, int n_in, void* d_out, int out_size) {
    static EncodeFn enc = nullptr;
    static int ncl = 0, nhelp = 0;
    const int ntok = in_sizes[0] / D;
    cudaLaunchConfig_t cfg = {};
    cudaLaunchAttribute at[1];
    at[0].id = cudaLaunchAttributeClusterDimension; at[0].val.clusterDim.x = CL; at[0].val.clusterDim.y = 1; at[0].val.clusterDim.z = 1;
    cfg.blockDim = dim3(NTHREADS); cfg.dynamicSmemBytes = SMEM_BYTES; cfg.attrs = at; cfg.numAttrs = 1; cfg.stream = cudaStreamPerThread;
    if (!enc) {
        cudaDriverEntryPointQueryResult qr; void* fn = nullptr;
        cudaGetDriverEntryPoint("cuTensorMapEncodeTiled", &fn, cudaEnableDefault, &qr);
        enc = (EncodeFn)fn;
        cudaFuncSetAttribute(spgemm_kernel<false>, cudaFuncAttributeMaxDynamicSharedMemorySize, SMEM_BYTES);
        cudaFuncSetAttribute(spgemm_kernel<true>, cudaFuncAttributeMaxDynamicSharedMemorySize, SMEM_BYTES);
        int dev = 0, nsm = 0;
        cudaGetDevice(&dev);
        cudaDeviceGetAttribute(&nsm, cudaDevAttrMultiProcessorCount, dev);
        cfg.gridDim = dim3(CL * (nsm / CL));
        cudaOccupancyMaxActiveClusters(&ncl, spgemm_kernel<false>, &cfg);
        if (ncl < 1) ncl = 1;
        nhelp = nsm > CL * ncl ? (nsm - CL * ncl) / CL : 0;
        if (nhelp > 7) nhelp = 7;
    }
    if (ntok % 4096 || ntok < 16384 || ntok > 65536 || ncl < 2 || ncl > 56 || ncl < CL * nhelp || 8 * (ncl + nhelp) > ntok / 64) {
        plain_kernel<<<(ntok + 7) / 8, 192, 0, cudaStreamPerThread>>>((const __nv_bfloat16*)d_in[0], (const __nv_bfloat16*)d_in[1], (const __nv_bfloat16*)d_in[2], (__nv_bfloat16*)d_out, ntok);
        return;
    }
    Maps maps;
    for (int v = 0; v < 2; v++) {
        const cuuint32_t rows = v == 0 ? 2 : 1;
        const cuuint64_t pitch = (v == 0 ? 14 : 57) * D * 2;
        {
            cuuint64_t dims[4] = {64, (cuuint64_t)ntok, 8 / rows, 9};
            cuuint64_t strides[3] = {D * 2, pitch, 128};
            cuuint32_t box[4] = {64, rows, 8 / rows, 9}, es[4] = {1, 1, 1, 1};
            enc(&maps.x[v], CU_TENSOR_MAP_DATA_TYPE_BFLOAT16, 4, d_in[0], dims, strides, box, es, CU_TENSOR_MAP_INTERLEAVE_NONE,
                CU_TENSOR_MAP_SWIZZLE_128B, CU_TENSOR_MAP_L2_PROMOTION_L2_128B, CU_TENSOR_MAP_FLOAT_OOB_FILL_NONE);
        }
        {
            cuuint64_t dims[3] = {D, (cuuint64_t)ntok, 8 / rows};
            cuuint64_t strides[2] = {D * 2, pitch};
            cuuint32_t box[3] = {64, rows, 8 / rows}, es[3] = {1, 1, 1};
            enc(&maps.o[v], CU_TENSOR_MAP_DATA_TYPE_BFLOAT16, 3, d_out, dims, strides, box, es, CU_TENSOR_MAP_INTERLEAVE_NONE,
                CU_TENSOR_MAP_SWIZZLE_128B, CU_TENSOR_MAP_L2_PROMOTION_NONE, CU_TENSOR_MAP_FLOAT_OOB_FILL_NONE);
        }
    }
    {
        cuuint64_t dims[3] = {256, (cuuint64_t)ntok * D * 2 / 2048, 4};
        cuuint64_t strides[2] = {2048, 16384};
        cuuint32_t box[3] = {256, 4, 4}, es[3] = {1, 1, 1};
        enc(&maps.pf, CU_TENSOR_MAP_DATA_TYPE_FLOAT64, 3, d_in[0], dims, strides, box, es, CU_TENSOR_MAP_INTERLEAVE_NONE,
            CU_TENSOR_MAP_SWIZZLE_NONE, CU_TENSOR_MAP_L2_PROMOTION_NONE, CU_TENSOR_MAP_FLOAT_OOB_FILL_NONE);
    }
    Params p;
    p.w = (const uint16_t*)d_in[1]; p.bias = (const uint16_t*)d_in[2]; p.x = (const uint8_t*)d_in[0];
    p.nq = ntok / 64; p.npages = (int)(((size_t)ntok * D * 2) >> 21);
    const int nc = ncl, nh = nhelp;
    p.ncl = nc; p.nh = nh; p.nctas = CL * (nc + nh);
    p.m0 = (nc + nh) * XEARLY / 2;
    for (int h = 0; h < 8; h++) {
        const uint32_t R = p.nq - p.m0, H = h * (HT * p.nq / 1024 * 44 / (nc + nh));
        p.ratio[h] = h <= nh ? (H << 16) / (R - H) : 0;
        p.rm[h] = p.ratio[h] ? (((R - 1) << 16) + 0x7FFFu) / (0x10000u + p.ratio[h]) + 1 : R;
    }
    p.c0 = (p.m0 * 9) >> 3;
    p.tb = p.m0 + (NSLOT - XEARLY) * (nc + nh) / 2;
    p.ta = p.tb + 1 + (int)((p.nq - p.tb) * TAFRAC); p.te = (int)(p.nq * TEFRAC) + 2;
    p.slope0 = ((LEAD1 - LEAD0) << 16) / (p.ta - p.tb); p.slope1 = ((LEAD1 - LEADE) << 16) / (p.te - p.ta);
    cfg.gridDim = dim3(CL * nc);
    cudaLaunchKernelEx(&cfg, spgemm_kernel<false>, p, maps);
    if (nh) {
        at[0].id = cudaLaunchAttributeProgrammaticStreamSerialization; at[0].val.programmaticStreamSerializationAllowed = 1;
        cfg.gridDim = dim3(CL * nh);
        cudaLaunchKernelEx(&cfg, spgemm_kernel<true>, p, maps);
    }
}
```

```cpp
#include <cuda_runtime.h>
#include <cuda_bf16.h>
#include <cuda.h>
#include <stdint.h>

constexpr int D = 576;
constexpr int NT = 32;
constexpr int NSLOT = 5;
constexpr int XEARLY = 2;
constexpr int NSTAT = 4;
constexpr int DELTA = 36;
constexpr int HT = 45;
constexpr int LEAD0 = 140, LEAD1 = 295, LEADE = 32, PACE = 1200;
constexpr double TAFRAC = 0.261, TEFRAC = 0.97;
constexpr int PWAIT = 1900;
constexpr int KSTEPS = 18;
constexpr int CL = 3;
constexpr int TILE_BYTES = NT * D * 2;
constexpr int STG_BYTES = NT * 128;
constexpr int NACC = NT / 2;
constexpr int NB = NT / 8;
constexpr int NCONS = 384;
constexpr int NTHREADS = 512;
constexpr int NTAB = 1024;
constexpr uint32_t NO_TILE = 0xFFFFFu;

constexpr int OFF_X = 0;
constexpr int OFF_WST = OFF_X + (NSLOT - 1) * TILE_BYTES;
constexpr int OFF_STG = OFF_X + NSLOT * TILE_BYTES;
constexpr int OFF_TAB = OFF_STG + 6 * STG_BYTES;
constexpr int OFF_TK = OFF_TAB + 16 * NTAB;
constexpr int OFF_MSK = OFF_TK + 128;
constexpr int OFF_SEL = OFF_MSK + 2 * 36 * 8;
constexpr int OFF_INFO = OFF_SEL + 128;
constexpr int OFF_FULL = OFF_INFO + 32;
constexpr int OFF_EMPTY = OFF_FULL + 8 * NSLOT;
constexpr int OFF_MBAR = OFF_EMPTY + 8 * NSLOT;
constexpr int OFF_GO = OFF_MBAR + 16;
constexpr int OFF_PLAN = OFF_GO + 8;
constexpr int OFF_PLAN2 = OFF_PLAN + 8;
constexpr int SMEM_BYTES = OFF_PLAN2 + 8 + 1024;
static_assert(SMEM_BYTES <= 232448 && TILE_BYTES >= 192 * 128 && XEARLY % 2 == 0 && XEARLY < NSLOT && NSLOT < 8 && NB == 4 && OFF_INFO % 16 == 0, "layout");

__device__ __align__(128) uint4    g_afrag[9 * (KSTEPS + 1) * 128];
__device__ __align__(128) uint4    g_aux[36 * 6 * 32];
__device__ __align__(128) uint2    g_rval[36 * 36 * 32];
__device__ __align__(128) uint32_t g_roff[36 * 36 * 32];
__device__ __align__(128) uint32_t g_ready[36 * 32];
__device__ __align__(128) uint32_t g_passed;
__device__ __align__(128) uint32_t g_ticket;
__device__ __align__(128) uint32_t g_hreg[3 * 32];
__device__ __align__(128) uint32_t g_done;
__device__ __align__(128) ulonglong2 g_plan;

__device__ __forceinline__ uint32_t max2(uint32_t a, uint32_t b) { uint32_t d; asm("max.u16x2 %0, %1, %2;" : "=r"(d) : "r"(a), "r"(b)); return d; }
__device__ __forceinline__ uint32_t min2(uint32_t a, uint32_t b) { uint32_t d; asm("min.u16x2 %0, %1, %2;" : "=r"(d) : "r"(a), "r"(b)); return d; }
__device__ __forceinline__ uint32_t sign2(uint32_t a) { uint32_t d; asm("prmt.b32 %0, %1, %1, 0xBB99;" : "=r"(d) : "r"(a)); return d; }
__device__ __forceinline__ void load_units(uint32_t wsm, int g4, int ulo, int uhi, int lane, uint32_t (&m)[4]) {
    const int row = g4 * 16 + ((lane & 7) >> 1) * 4 + ((lane >> 3) & 1) * 2 + (lane & 1);
    const uint32_t ad = wsm + row * 128 + (((lane < 16 ? ulo : uhi) ^ ((row & 1) | ((row >> 1) & 6))) << 4);
    asm volatile("ldmatrix.sync.aligned.m8n8.x4.trans.shared.b16 {%0,%1,%2,%3}, [%4];" : "=r"(m[0]), "=r"(m[1]), "=r"(m[2]), "=r"(m[3]) : "r"(ad) : "memory");
}
__device__ __forceinline__ void zip4(uint32_t a01, uint32_t a23, uint32_t b01, uint32_t b23, uint32_t (&x)[4]) {
    x[0] = __byte_perm(a01, b01, 0x5410); x[1] = __byte_perm(a01, b01, 0x7632); x[2] = __byte_perm(a23, b23, 0x5410); x[3] = __byte_perm(a23, b23, 0x7632);
}
__device__ __forceinline__ void middle2(const uint32_t (&x)[4], uint32_t (&m)[4], uint32_t& u, uint32_t& v) {
#pragma unroll
    for (int i = 0; i < 4; i++) m[i] = x[i] & 0x7FFF7FFFu;
    u = min2(max2(m[0], m[1]), max2(m[2], m[3])); v = max2(min2(m[0], m[1]), min2(m[2], m[3]));
}
__device__ __forceinline__ int ties(uint32_t x0, uint32_t x1, uint32_t x2, uint32_t x3) {
    const uint32_t x[4] = {x0, x1, x2, x3};
    uint32_t m[4], u, v;
    middle2(x, m, u, v);
    const uint32_t t = u ^ v, f = u ^ min2(min2(m[0], m[1]), min2(m[2], m[3]));
    const bool t0 = (t & 0xFFFFu) == 0 && (v & 0xFFFFu) != 0, t1 = t < 0x10000u && v >= 0x10000u;
    return t0 + t1 + 2 * ((t0 && (f & 0xFFFFu) == 0) || (t1 && f < 0x10000u));
}
__device__ __forceinline__ void split(const uint32_t (&x)[4], bool dbl, bool P, uint32_t& alo, uint32_t& ahi, uint32_t& nib, uint32_t& va, uint32_t& vb) {
    uint32_t m[4], u, v;
    middle2(x, m, u, v);
    const uint32_t c = 0x80008000u - max2(max2(u, v), 0x00010001u);
    uint32_t k0 = sign2(m[0] + c), k1 = sign2(m[1] + c), k2 = sign2(m[2] + c), k3 = sign2(m[3] + c);
    const uint32_t three = (k0 & k1 & (k2 | k3)) | (k2 & k3 & (k0 | k1)), four = k0 & k1 & k2 & k3;
    const bool a2 = !dbl && P;
    const uint32_t pa = a2 ? k2 : k0, pb = dbl ? k2 : P ? k3 : k1;
    const uint32_t ra = three & pa, rb = three & pb & (four | ~pa);
    va = (a2 ? x[2] : x[0]) & ra; vb = (dbl ? x[2] : P ? x[3] : x[1]) & rb;
    if (a2) k2 &= ~ra; else k0 &= ~ra;
    if (dbl) k2 &= ~rb; else if (P) k3 &= ~rb; else k1 &= ~rb;
    const uint32_t s1 = k1 & k0, s2 = k2 & (k0 | k1);
    const uint32_t t = (k1 & x[1]) | (~k1 & k2 & x[2]);
    const uint32_t x0 = (k0 & x[0]) | (~k0 & t), x1 = (s1 & x[1]) | (s2 & x[2]) | (k3 & x[3]);
    nib = (~k0 & k1 & 0x00010001u) | (~k0 & ~k1 & 0x00020002u) | (~s2 & 0x00040004u) | (~s1 & 0x00080008u);
    alo = __byte_perm(x0, x1, 0x5410); ahi = __byte_perm(x0, x1, 0x7632);
}
__device__ __forceinline__ uint32_t resid_off(int g, int P, int r) {
    int k0 = 4 * g + 2 * P;
    int chunk = k0 >> 6, byte = (k0 & 63) * 2;
    return chunk * 1024 + r * 128 + (((byte >> 4) ^ r) << 4) + (byte & 15);
}
__device__ __forceinline__ void emit_half(const uint32_t (&wm)[4], uint32_t md, int rb, int ks, int e, int lane, uint32_t units, uint32_t b0, uint32_t b1) {
    uint32_t* const aux = (uint32_t*)(g_aux + rb * 6 * 32);
    auto put_slot = [&](int j, int ln, uint32_t v, uint32_t off) {
        uint16_t* o = j < 6 ? (uint16_t*)aux + (3 * 32 + ln) * 8 + j : (uint16_t*)g_roff + ((rb * 36 + (j >> 1)) * 32 + ln) * 2 + (j & 1);
        uint16_t* w = j < 6 ? (uint16_t*)aux + ((4 + (j >> 2)) * 32 + ln) * 8 + (j & 2) * 2 + (j & 1) : (uint16_t*)g_rval + ((rb * 36 + (j >> 1)) * 32 + ln) * 4 + (j & 1);
        o[0] = (uint16_t)off; w[0] = (uint16_t)v; w[2] = (uint16_t)(v >> 16);
    };
    const int r = lane >> 2, q = lane & 3, g = 4 * e + q, twice = units >> 8;
    const uint32_t gm = __shfl_sync(~0u, md, ks);
    const uint32_t c2 = __popc(md & 0x5555u) | (__popc(md & 0xAAAAu) << 16);
    const uint32_t tot = __reduce_add_sync(~0u, c2), pre = __reduce_add_sync(~0u, lane < ks ? c2 : 0u);
    const int ne = tot & 0xFFFF, no = tot >> 16;
    const int rk = ((q & 1) ? pre >> 16 : pre & 0xFFFF) + __popc(gm & ((q & 1) ? 0xAAAAu : 0x5555u) & (((1u << g) - 1) * 0x101u));
    const bool dbl = (gm >> (8 + g)) & 1;
    uint32_t a0, a1, va, vb, x[4], nib;
    zip4(wm[0], wm[1], wm[2], wm[3], x); split(x, dbl, rk & 1 && ks != twice, a0, a1, nib, va, vb);
    uint2* const frag = (uint2*)(g_afrag + (rb >> 2) * (KSTEPS + 1) * 128 + (rb & 3) * 32 + lane) + e;
    frag[ks * 256] = make_uint2(a0, a1);
    if (ks == (twice < KSTEPS ? twice : 0)) frag[KSTEPS * 256] = twice < KSTEPS ? make_uint2(__byte_perm(va, vb, 0x5410), __byte_perm(va, vb, 0x7632)) : make_uint2(0, 0);
    nib <<= 4 * q;
    nib |= __shfl_xor_sync(~0u, nib, 1);
    nib |= __shfl_xor_sync(~0u, nib, 2);
    if (q == 2 * (ks & 1) + e) aux[((ks >> 3) * 32 + lane) * 4 + ((ks >> 1) & 3)] = nib;
    const int em = min(ne, max(8, 16 - no)), om = min(no, 16 - em);
    const int odd = q & 1, m = odd ? om : em;
    auto place = [&](int k) {
        const int t = 15 - k;
        return k >= m ? 16 + (odd ? ne - em : 0) + k - m : k < 8 ? (k >> 1) * 4 + 2 * odd + (k & 1) : (t >> 1) * 4 + 2 * (odd ^ 1) + (t & 1);
    };
    const uint32_t second = (__ballot_sync(~0u, vb != 0) & (0x11111111u << q)) != 0 && !dbl;
    if ((gm >> g) & 1) {
        const int sl = place(rk);
        put_slot(sl >> 2, r * 4 + (sl & 3), !dbl ? va | vb : (rk & 1) ? vb : va, resid_off(ks * 8 + g, rk & 1, r) | (second << 15));
        if (dbl) { const int s2 = place(rk + 1); put_slot(s2 >> 2, r * 4 + (s2 & 3), (rk & 1) ? va : vb, resid_off(ks * 8 + g, ~rk & 1, r)); }
    }
    const int ntot = ne + no, z = 2 * ks + e;
    const int ng = ntot > 16 ? (ntot + 3) >> 2 : min(4, (max(ne, no) + 1) >> 1);
    if (z == 8) {
        const int ulo = units & 7, uhi = (units >> 4) & 7;
        aux[(2 * 32 + lane) * 4 + 1] = ng | (units << 8);
        *(uint2*)(aux + (2 * 32 + lane) * 4 + 2) = make_uint2(__shfl_sync(~0u, ulo < 4 ? b0 : b1, (ulo * 8 + r) & 31) * 0x10001u, __shfl_sync(~0u, uhi < 4 ? b0 : b1, (uhi * 8 + r) & 31) * 0x10001u);
        aux[(3 * 32 + lane) * 4 + 3] = 0; *(uint2*)(aux + (5 * 32 + lane) * 4 + 2) = make_uint2(0, 0);
    }
    const int idx = 2 * z + (q & 1);
    const int frow = z < 6 ? z : z == 6 ? ng - 1 : ng;
    const bool fill = z < 4 ? !(idx < ((q >> 1) ? om : em) || (15 - idx) < ((q >> 1) ? em : om))
                            : (z < 6 || (ng > 6 && (z == 6 || (z == 7 && (ng & 1))))) && 4 * frow + q >= ntot;
    if (fill) put_slot(frow, lane, 0, resid_off(q >> 1, q & 1, r));
}

template<int SEL> __device__ __forceinline__ void wgmma_sp(float (&d)[NACC], const uint32_t (&a)[4], uint64_t bdesc, uint32_t meta) {
    asm volatile("{\n.reg .pred p;\nsetp.ne.b32 p, %22, 0;\n"
        "wgmma.mma_async.sp.sync.aligned.m64n32k32.f32.bf16.bf16 {%0, %1, %2, %3, %4, %5, %6, %7, %8, %9, %10, %11, %12, %13, %14, %15}, {%16, %17, %18, %19}, %20, %21, %23, p, 1, 1, 0;\n}\n"
        : "+f"(d[0]), "+f"(d[1]), "+f"(d[2]), "+f"(d[3]), "+f"(d[4]), "+f"(d[5]), "+f"(d[6]), "+f"(d[7]), "+f"(d[8]), "+f"(d[9]), "+f"(d[10]), "+f"(d[11]), "+f"(d[12]), "+f"(d[13]), "+f"(d[14]), "+f"(d[15])
        : "r"(a[0]), "r"(a[1]), "r"(a[2]), "r"(a[3]), "l"(bdesc), "r"(meta), "r"(1), "n"(SEL));
}

__device__ __forceinline__ void mbar_init(uint32_t bar, uint32_t cnt) { asm volatile("mbarrier.init.shared::cta.b64 [%0], %1;" :: "r"(bar), "r"(cnt) : "memory"); }
__device__ __forceinline__ void mbar_expect_tx(uint32_t bar, uint32_t bytes) {
    asm volatile("mbarrier.arrive.expect_tx.shared::cta.b64 _, [%0], %1;" :: "r"(bar), "r"(bytes) : "memory");
}
__device__ __forceinline__ void mbar_arrive(uint32_t bar) { asm volatile("mbarrier.arrive.shared::cta.b64 _, [%0];" :: "r"(bar) : "memory"); }
__device__ __forceinline__ void mbar_arrive_cluster(uint32_t bar) { asm volatile("mbarrier.arrive.shared::cluster.b64 _, [%0];" :: "r"(bar) : "memory"); }
__device__ __forceinline__ bool mbar_try(uint32_t bar, uint32_t parity) {
    uint32_t ok;
    asm volatile("{\n.reg .pred p;\nmbarrier.try_wait.parity.shared::cta.b64 p, [%1], %2;\nselp.u32 %0, 1, 0, p;\n}\n" : "=r"(ok) : "r"(bar), "r"(parity) : "memory");
    return ok;
}
__device__ __forceinline__ bool mbar_test(uint32_t bar, uint32_t parity) {
    uint32_t ok;
    asm volatile("{\n.reg .pred p;\nmbarrier.test_wait.parity.shared::cta.b64 p, [%1], %2;\nselp.u32 %0, 1, 0, p;\n}\n" : "=r"(ok) : "r"(bar), "r"(parity) : "memory");
    return ok;
}
__device__ __forceinline__ void fail_if(bool c) { asm volatile("{\n.reg .pred p;\nsetp.ne.u32 p, %0, 0;\n@p st.volatile.global.u32 [%1], %0;\n}\n" :: "r"((uint32_t)c), "l"(0ull) : "memory"); }
__device__ __forceinline__ void mbar_wait(uint32_t bar, uint32_t parity) {
    int n = 0;
    while (!mbar_try(bar, parity)) fail_if(++n > (1 << 20));
}
__device__ __forceinline__ void st_async(uint32_t addr, uint32_t v, uint32_t bar) {
    asm volatile("st.async.weak.shared::cluster.mbarrier::complete_tx::bytes.u32 [%0], %1, [%2];" :: "r"(addr), "r"(v), "r"(bar) : "memory");
}
__device__ __forceinline__ uint32_t mapa(uint32_t a, uint32_t cta) { uint32_t d; asm("mapa.shared::cluster.u32 %0, %1, %2;" : "=r"(d) : "r"(a), "r"(cta)); return d; }
__device__ __forceinline__ uint32_t lds32(uint32_t a) { uint32_t v; asm volatile("ld.shared.b32 %0, [%1];" : "=r"(v) : "r"(a)); return v; }
__device__ __forceinline__ uint32_t lds32v(uint32_t a) { uint32_t v; asm volatile("ld.volatile.shared.b32 %0, [%1];" : "=r"(v) : "r"(a) : "memory"); return v; }
__device__ __forceinline__ void sts32(uint32_t a, uint32_t v) { asm volatile("st.shared.b32 [%0], %1;" :: "r"(a), "r"(v) : "memory"); }
__device__ __forceinline__ uint4 ldw(const uint4* a) { uint4 v; asm volatile("ld.weak.global.L1::no_allocate.v4.u32 {%0,%1,%2,%3}, [%4];" : "=r"(v.x), "=r"(v.y), "=r"(v.z), "=r"(v.w) : "l"(a) : "memory"); return v; }
__device__ __forceinline__ void mma_k8(float* c, uint2 a, uint32_t b) {
    asm volatile("mma.sync.aligned.m16n8k8.row.col.f32.bf16.bf16.f32 {%0,%1,%2,%3}, {%4,%5}, {%6}, {%0,%1,%2,%3};"
                 : "+f"(c[0]), "+f"(c[1]), "+f"(c[2]), "+f"(c[3]) : "r"(a.x), "r"(a.y), "r"(b));
}
__device__ __forceinline__ void mma_k16(float* d, uint2 a, uint2 a2, uint32_t b0, uint32_t b1, float c0, float c1, float c2, float c3) {
    asm volatile("mma.sync.aligned.m16n8k16.row.col.f32.bf16.bf16.f32 {%0,%1,%2,%3}, {%4,%5,%6,%7}, {%8,%9}, {%10,%11,%12,%13};"
                 : "=f"(d[0]), "=f"(d[1]), "=f"(d[2]), "=f"(d[3]) : "r"(a.x), "r"(a.y), "r"(a2.x), "r"(a2.y), "r"(b0), "r"(b1), "f"(c0), "f"(c1), "f"(c2), "f"(c3));
}
__device__ __forceinline__ uint32_t pack_bias(float lo, float hi, uint32_t bias2) {
    uint32_t p, o;
    asm("cvt.rn.bf16x2.f32 %0, %1, %2;" : "=r"(p) : "f"(hi), "f"(lo));
    asm("add.rn.bf16x2 %0, %1, %2;" : "=r"(o) : "r"(p), "r"(bias2));
    return o;
}

template <bool B> struct Flag { static constexpr bool value = B; };
struct Params {
    const uint16_t* w; const uint16_t* bias; const uint8_t* x;
    int nq, npages;
    int ncl, nh;
    int nctas;
    int tb, ta, te, slope0, slope1, c0;
    int m0;
    uint32_t ratio[8]; int rm[8];
};
struct Maps { CUtensorMap x[2], o[2], pf; };
__device__ __forceinline__ uint4 entry_w(int M, int w, int q, int extra) {
    const int r = M - (M >> 6), o = (r * 9363) >> 16, t = r - 7 * o, odd = t & 1, n = t >> 1;
    const int u = w ^ o ^ odd;
    const int C = 8 * o + 2 * n + ((n ^ u) & 1), C2 = 8 * o + 6 + ((1 ^ u) & 1);
    const uint32_t ra = 57 * C - ((C * 7282) >> 16) + 4 * odd, rb = odd ? 57 * C2 - ((C2 * 7282) >> 16) + 4 + 2 * n : ra + 12;
    const uint32_t rm = 2048 * (2 * (M >> 6) + w) + 56;
    const bool mixed = (M & 63) == 63;
    return make_uint4(M | (mixed << 14) | (q << 17) | (extra << 18), mixed ? rm * 0x10001u + (512u << 16) : ra * 0x10001u + (2u << 16),
                      mixed ? rm * 0x10001u + (1024u | 1536u << 16) : (ra + (odd ? 4 : 10)) | (rb << 16), 0);
}
__device__ __forceinline__ uint4 entry(int M, int q, int extra, unsigned long long plan) {
    const int r = M - (M >> 6), page = (r * 2341) >> 16;
    return entry_w(M, (M & 63) == 63 ? q : q ^ (int)((plan >> page) & 1), q, extra);
}
__device__ __forceinline__ int frontier(const Params& p, int t) {
    t = max(t, p.tb);
    const int l = t < p.ta ? LEAD0 + ((p.slope0 * (t - p.tb)) >> 16) : LEADE + max(0, (p.slope1 * (p.te - t)) >> 16);
    return (min(p.nq, t + l) * 9) >> 3;
}
__device__ __forceinline__ uint4 cl_entry(const Params& p, int m, int q, uint32_t ratio, unsigned long long plan) {
    const int nb = (m * ratio + 0x8000u) >> 16, nb1 = m ? ((m - 1) * ratio + 0x8000u) >> 16 : 0;
    uint4 e = entry(p.m0 + m + nb, q, nb - nb1, plan);
    const int c0 = frontier(p, p.m0 + m - 1 + nb1);
    e.w = c0 | (frontier(p, p.m0 + m + nb) - c0) << 16;
    return e;
}
__device__ __forceinline__ int helpers(const Params& p, unsigned long long plan, int q) {
    const int h0 = min(max(((p.ncl + p.nh) >> 1) - (p.ncl - (int)((plan >> 48) & 0xFF)), 0), p.nh);
    return q ? p.nh - h0 : h0;
}
__device__ __forceinline__ void draw(uint32_t& v, uint32_t* ctr, uint32_t inc) {
    asm volatile("{\n.reg .pred p;\nelect.sync _|p, 0xffffffff;\n@p atom.relaxed.gpu.global.add.u32 %0, [%1], %2;\n}" : "+r"(v) : "l"(ctr), "r"(inc) : "memory");
}
__device__ __forceinline__ uint4 lds128v(uint32_t a) { uint4 v; asm volatile("ld.volatile.shared.v4.b32 {%0,%1,%2,%3}, [%4];" : "=r"(v.x), "=r"(v.y), "=r"(v.z), "=r"(v.w) : "r"(a) : "memory"); return v; }
__device__ __forceinline__ void sts128(uint32_t a, uint4 e) { asm volatile("st.shared.v4.b32 [%0], {%1,%2,%3,%4};" :: "r"(a), "r"(e.x), "r"(e.y), "r"(e.z), "r"(e.w) : "memory"); }

__device__ __forceinline__ const uint8_t* probe_line(const Params& p, int page, int cell, int line, int parity) {
    return p.x + ((size_t)page << 21) + cell * 65536 + ((__popc(cell & 0xB) ^ parity) & 1) * 4096 + line * 128;
}
__device__ __forceinline__ int lag(const uint8_t* first, const uint8_t* second, uint32_t scratch, uint32_t since) {
    uint32_t t0, t1;
#pragma unroll 1
    for (int e = 0; e < 2; e++) {
        uint32_t a = 0, b = 0;
        asm volatile("{\n.reg .pred p;\nsetp.ne.s32 p, %4, 0;\n@p ld.global.cg.u32 %0, [%2];\n@p ld.global.cg.u32 %1, [%3];\n}"
                     : "+r"(a), "+r"(b) : "l"(first), "l"(second), "r"(e) : "memory");
        asm volatile("st.volatile.shared.u32 [%0], %1;" :: "r"(scratch), "r"(a) : "memory");
        asm volatile("mov.u32 %0, %%clock;" : "=r"(t0) :: "memory");
        asm volatile("st.volatile.shared.u32 [%0], %1;" :: "r"(scratch), "r"(b) : "memory");
        asm volatile("mov.u32 %0, %%clock;" : "=r"(t1) :: "memory");
        uint32_t t = t1;
        while (t - since < PWAIT) asm volatile("mov.u32 %0, %%clock;" : "=r"(t) :: "memory");
    }
    return t1 - t0;
}

template <bool HELPER>
__global__ void __launch_bounds__(NTHREADS, 1)
spgemm_kernel(const __grid_constant__ Params p, const __grid_constant__ Maps maps) {
    extern __shared__ unsigned char smem_raw[];
    const uint32_t sb = ((uint32_t)__cvta_generic_to_shared(smem_raw) + 1023u) & ~1023u;
    const int tid = threadIdx.x, warp = __shfl_sync(~0u, tid >> 5, 0), lane = tid & 31;
    const int rank = blockIdx.x % CL, cid = blockIdx.x / CL;
    const uint32_t bar_full = sb + OFF_FULL, bar_empty = sb + OFF_EMPTY, tk = sb + OFF_TK;
    const int pr = HELPER ? 2 : rank, pc = HELPER ? blockIdx.x : cid;
    const uint8_t* pl = probe_line(p, pr == 1 ? min(pc, p.npages - 1) : p.npages - 1, pr == 1 ? 30 : pc & 31,
                                   (pr == 1 ? 4 + 2 * max(pc + 1 - p.npages, 0) : pr * 15 + (pc >> 5) * 2) + (warp & 1), warp & 1);
    uint32_t tp;
    asm volatile("mov.u32 %0, %%clock;" : "=r"(tp) :: "memory");
    if (!HELPER && warp >= 14 && lane < 2) asm volatile("prefetch.global.L2 [%0];" :: "l"((const uint8_t*)((uintptr_t)pl ^ (lane << 12))) : "memory");
    uint4 wv[4];
    const int wrow = warp * 16 + (lane & 3) * 4;
    uint32_t b0, b1;
    auto prep_load = [&](int mtile) {
        b0 = __ldg(p.bias + mtile * 64 + lane); b1 = __ldg(p.bias + mtile * 64 + 32 + lane);
#pragma unroll
        for (int j = 0; j < 4; j++) wv[j] = __ldg((const uint4*)(p.w + (rank * 192 + wrow + j) * D + mtile * 64 + (lane >> 2) * 8));
    };
    if (!HELPER && warp < 12) {
        if (cid < 36) prep_load(cid >> 2);
        asm volatile("barrier.cluster.arrive.relaxed.aligned;" ::: "memory");
    }

    if (warp >= 12) {
        asm volatile("setmaxnreg.dec.sync.aligned.u32 32;");
        if (tid == NCONS) {
#pragma unroll
            for (int s = 0; s < NSLOT; s++) { mbar_init(bar_full + 8 * s, 1); mbar_init(bar_empty + 8 * s, HELPER ? 3 : 3 * CL); }
#pragma unroll
            for (int j = 0; j < 8; j++) sts32(tk + 16 * j, 0);
            mbar_init(sb + OFF_MBAR, 1); mbar_init(sb + OFF_MBAR + 8, 1);
            mbar_init(sb + OFF_GO, HELPER ? 12 : 12 + CL); mbar_init(sb + OFF_PLAN, 1); mbar_init(sb + OFF_PLAN2, 1);
            asm volatile("fence.mbarrier_init.release.cluster;" ::: "memory");
            mbar_expect_tx(sb + OFF_MBAR, 36 * 8);
            if (!HELPER && rank != 0) mbar_expect_tx(sb + OFF_PLAN, 16);
        }
        if (tid == NCONS + 32) {
            asm volatile("prefetch.tensormap [%0];" :: "l"(&maps.x[0]) : "memory");
            if (!HELPER) asm volatile("griddepcontrol.launch_dependents;");
            asm volatile("prefetch.tensormap [%0];" :: "l"(&maps.pf) : "memory");
            asm volatile("prefetch.tensormap [%0];" :: "l"(&maps.x[1]) : "memory");
#pragma unroll
            for (int j = 0; j < 2; j++) asm volatile("prefetch.tensormap [%0];" :: "l"(&maps.o[j]) : "memory");
        }
        __syncwarp();
        auto wait_plan = [&]() -> uint4 {
            unsigned long long a, b; int n = 0;
            do { asm volatile("ld.relaxed.gpu.global.v2.u64 {%0, %1}, [%2];" : "=l"(a), "=l"(b) : "l"(&g_plan) : "memory"); fail_if(++n > (1 << 22)); }
            while (__any_sync(~0u, (int)(a >> 56) + (int)(b >> 56) != 2 * p.ncl));
            b &= (1ull << 56) - 1;
            const int side = (b >> cid) & 1, n1 = __popcll(b), below = __popcll(b & ((1ull << cid) - 1));
            a = ((a ^ b) & ((1ull << 40) - 1)) | (unsigned long long)n1 << 48;
            return make_uint4((uint32_t)a, (uint32_t)(a >> 32), side | (side ? below : cid - below) << 8 | (side ? n1 : p.ncl - n1) << 16, 0);
        };
        auto measure = [&](uint32_t since) -> int {
            const int d = lag(pl, (const uint8_t*)((uintptr_t)pl ^ 4096), sb + OFF_INFO + 16 + 4 * (warp & 1), since);
            if (warp == 14 && lane == 0) sts32(sb + OFF_INFO + 24, d);
            asm volatile("bar.sync 11, 64;" ::: "memory");
            return d > (int)lds32v(sb + OFF_INFO + 24);
        };
        uint4 e0 = make_uint4(0, 0, 0, 0), e1 = e0;
        if (HELPER) {
            asm volatile("bar.sync 0;" ::: "memory");
            int side = 0;
            if (warp >= 14) side = measure(tp - PWAIT);
            if (warp == 15) {
                uint32_t old = 0;
                if (lane == 0) {
                    old = atomicAdd(&g_hreg[rank * 32], side ? 0x10000u : 1u);
                    if ((old & 0xFFFF) + (old >> 16) == p.nh - 1) g_hreg[rank * 32] = 0;
                }
                const uint4 inf = wait_plan();
                const unsigned long long plan = inf.x | ((unsigned long long)inf.y << 32);
                old = __shfl_sync(~0u, old, 0);
                int idx = side ? p.nh - 1 - (old >> 16) : old & 0xFFFF, nh = helpers(p, plan, 0), q = 0;
                if (idx >= nh) { idx -= nh; nh = p.nh - nh; q ^= 1; }
                const uint32_t ratio = p.ratio[nh];
                const int rm = p.rm[nh], H = p.nq - p.m0 - rm;
                for (int j0 = 0; __any_sync(~0u, idx + (j0 - 1) * nh < H); j0 += 32) {
                    const int k = idx + (j0 + lane) * nh, mk = (((k + 1) << 16) - 0x8000u + ratio - 1) / ratio;
                    uint4 e = entry(p.m0 + min(mk, rm) + k, q, 0, plan);
                    if (k >= H) e.x = NO_TILE;
                    sts128(sb + OFF_TAB + 16 * (j0 + lane), e);
                }
                __syncwarp();
                if (lane == 0) mbar_arrive(sb + OFF_PLAN);
            }
        } else {
            asm volatile("barrier.cluster.arrive.relaxed.aligned;" ::: "memory");
            if (warp == 12) { e0 = entry_w(cid, 0, 0, 0); e1 = entry_w(cid, 1, 1, 0); }
            if (rank < 2 && warp >= 14) {
                const int side = measure(tp);
                if (warp == 15 && lane == 0) asm volatile("red.relaxed.gpu.global.add.u64 [%0], %1;" :: "l"(rank ? &g_plan.x : &g_plan.y), "l"((1ull << 56) | (unsigned long long)side << cid) : "memory");
            }
            asm volatile("barrier.cluster.wait.aligned;" ::: "memory");
            if (warp >= 13) {
                if (warp == 15 && rank == 0) {
                    const uint4 inf = wait_plan();
                    if (lane == 0) sts128(sb + OFF_INFO, inf);
                    else if (lane < CL)
                        asm volatile("st.async.weak.shared::cluster.mbarrier::complete_tx::bytes.v4.u32 [%0], {%1, %2, %3, %4}, [%5];"
                                     :: "r"(mapa(sb + OFF_INFO, lane)), "r"(inf.x), "r"(inf.y), "r"(inf.z), "r"(inf.w), "r"(mapa(sb + OFF_PLAN, lane)) : "memory");
                }
                if (rank == 0) asm volatile("bar.sync 15, 96;" ::: "memory"); else mbar_wait(sb + OFF_PLAN, 0);
                const uint4 inf = lds128v(sb + OFF_INFO);
                const unsigned long long plan = inf.x | ((unsigned long long)inf.y << 32);
                const int nh = helpers(p, plan, inf.z & 1), rm = p.rm[nh], nc = inf.z >> 16;
                const uint32_t ratio = p.ratio[nh];
                if (warp == 15 && rank == 0) {
                    const int m = ((inf.z >> 8) & 0xFF) + min(lane, NSTAT - 1) * nc;
                    sts128(sb + OFF_TAB + 16 * m, cl_entry(p, m, inf.z & 1, ratio, plan));
                    __syncwarp();
                    if (lane == 0) { mbar_arrive(sb + OFF_PLAN); mbar_expect_tx(sb + OFF_PLAN2, 16 * (rm - NSTAT * nc)); }
                }
                const uint32_t rtab = mapa(sb + OFF_TAB, 0), rbar = mapa(sb + OFF_PLAN2, 0);
                for (int m0 = NSTAT * nc + 96 * (2 - rank); __any_sync(~0u, m0 < rm); m0 += 288) {
                    const int m = m0 + tid - (NCONS + 32);
                    const uint4 e = cl_entry(p, m, inf.z & 1, ratio, plan);
                    if (m < rm) asm volatile("st.async.weak.shared::cluster.mbarrier::complete_tx::bytes.v4.u32 [%0], {%1, %2, %3, %4}, [%5];"
                                             :: "r"(rtab + 16 * m), "r"(e.x), "r"(e.y), "r"(e.z), "r"(e.w), "r"(rbar) : "memory");
                }
            }
        }
        if (warp == 12) {
            if (!HELPER && rank != 0) {
                mbar_wait(sb + OFF_PLAN, 0);
                const uint4 inf = lds128v(sb + OFF_INFO);
                const unsigned long long plan = inf.x | ((unsigned long long)inf.y << 32);
                auto cell = [&](int c, int q) {
                    const int y = 32 * c - 2 + 4 * ((__popc(c & 0xB) ^ (int)(plan >> (c >> 5)) ^ q) & 1);
                    asm volatile("{\n.reg .pred p;\nelect.sync _|p, 0xffffffff;\n@p cp.async.bulk.prefetch.tensor.3d.L2.global.tile [%0, {%1, %2, %1}];\n}" :: "l"(&maps.pf), "r"(0), "r"(y) : "memory");
                };
                const int fe0 = frontier(p, 0), step = 2 * (inf.z >> 16);
                int u0 = p.c0 + 2 * ((inf.z >> 8) & 0xFF) + rank - 1;
                {
                    uint32_t t, due;
                    asm volatile("mov.u32 %0, %%clock;" : "=r"(due) :: "memory");
                    due += (PACE * (u0 - p.c0)) / step;
                    for (; __any_sync(~0u, u0 < fe0); u0 += step, due += PACE) {
                        do { asm volatile("mov.u32 %0, %%clock;" : "=r"(t) :: "memory"); } while (__any_sync(~0u, (int)(t - due) < 0));
                        cell(u0, inf.z & 1);
                    }
                }
                for (int j = XEARLY + rank - 1;; j += 2) {
                    uint4 v; uint32_t ahead;
                    for (int n = 0; __any_sync(~0u, (ahead = (((v = lds128v(tk + ((j & 7) << 4))).x >> 20) - (j + 1)) & 0xFFF) >= 0x800); n++) {
                        if (__any_sync(~0u, lds32v(tk + (((j - 1) & 7) << 4)) == (NO_TILE | (uint32_t)j << 20))) { v.x = NO_TILE; break; }
                        __nanosleep(100); fail_if(n > (1 << 24));
                    }
                    if (__any_sync(~0u, (v.x & NO_TILE) == NO_TILE)) break;
                    j += __reduce_max_sync(~0u, ahead);
                    for (int u = v.w & 0xFFFF; __any_sync(~0u, u < (v.w & 0xFFFF) + (v.w >> 16)); u++) cell(u, (v.x >> 17) & 1);
                }
            } else {
                const uint32_t rtk = HELPER ? tk : mapa(tk, lane < CL ? lane : 0), rfull = HELPER ? bar_full : mapa(bar_full, lane < CL ? lane : 0);
                int s = 0; uint32_t ph = 1;
                uint64_t pol;
                if (!HELPER) asm volatile("createpolicy.fractional.L2::evict_first.b64 %0, 1.0;" : "=l"(pol));
                else asm volatile("createpolicy.fractional.L2::evict_normal.b64 %0, 1.0;" : "=l"(pol));
                auto request = [&](int j, const uint4& t) {
                    const bool valid = t.x != NO_TILE;
                    const CUtensorMap* tm = &maps.x[(t.x >> 14) & 1];
                    mbar_wait(bar_empty + 8 * s, ph);
                    if (__any_sync(~0u, valid)) {
                        const uint32_t dst = sb + OFF_X + s * TILE_BYTES;
                        if (HELPER)
                            asm volatile("{\n.reg .pred p;\nelect.sync _|p, 0xffffffff;\n"
                                         "@p cp.async.bulk.tensor.4d.shared::cluster.global.mbarrier::complete_tx::bytes.L2::cache_hint [%0], [%4, {%6, %7, %6, %6}], [%5], %11;\n"
                                         "@p cp.async.bulk.tensor.4d.shared::cluster.global.mbarrier::complete_tx::bytes.L2::cache_hint [%1], [%4, {%6, %8, %6, %6}], [%5], %11;\n"
                                         "@p cp.async.bulk.tensor.4d.shared::cluster.global.mbarrier::complete_tx::bytes.L2::cache_hint [%2], [%4, {%6, %9, %6, %6}], [%5], %11;\n"
                                         "@p cp.async.bulk.tensor.4d.shared::cluster.global.mbarrier::complete_tx::bytes.L2::cache_hint [%3], [%4, {%6, %10, %6, %6}], [%5], %11;\n}\n"
                                         :: "r"(dst), "r"(dst + 9216), "r"(dst + 2 * 9216), "r"(dst + 3 * 9216), "l"(tm), "r"(bar_full + 8 * s), "r"(0),
                                            "r"(t.y & 0xFFFF), "r"(t.y >> 16), "r"(t.z & 0xFFFF), "r"(t.z >> 16), "l"(pol) : "memory");
                        else
                            asm volatile("{\n.reg .pred p;\nelect.sync _|p, 0xffffffff;\n"
                                         "@p cp.async.bulk.tensor.4d.shared::cluster.global.mbarrier::complete_tx::bytes.multicast::cluster.L2::cache_hint [%0], [%4, {%6, %7, %6, %6}], [%5], %11, %12;\n"
                                         "@p cp.async.bulk.tensor.4d.shared::cluster.global.mbarrier::complete_tx::bytes.multicast::cluster.L2::cache_hint [%1], [%4, {%6, %8, %6, %6}], [%5], %11, %12;\n"
                                         "@p cp.async.bulk.tensor.4d.shared::cluster.global.mbarrier::complete_tx::bytes.multicast::cluster.L2::cache_hint [%2], [%4, {%6, %9, %6, %6}], [%5], %11, %12;\n"
                                         "@p cp.async.bulk.tensor.4d.shared::cluster.global.mbarrier::complete_tx::bytes.multicast::cluster.L2::cache_hint [%3], [%4, {%6, %10, %6, %6}], [%5], %11, %12;\n}\n"
                                         :: "r"(dst), "r"(dst + 9216), "r"(dst + 2 * 9216), "r"(dst + 3 * 9216), "l"(tm), "r"(bar_full + 8 * s), "r"(0),
                                            "r"(t.y & 0xFFFF), "r"(t.y >> 16), "r"(t.z & 0xFFFF), "r"(t.z >> 16), "h"((uint16_t)((1u << CL) - 1)), "l"(pol) : "memory");
                    }
                    if (HELPER) {
                        if (lane == 0) { sts128(tk + ((j & 7) << 4), t); mbar_expect_tx(bar_full + 8 * s, valid ? TILE_BYTES : 0); }
                    } else if (lane < CL) {
                        asm volatile("mbarrier.arrive.expect_tx.shared::cluster.b64 _, [%0], %1;" :: "r"(rfull + 8 * s), "r"(valid ? TILE_BYTES + 16 : 16) : "memory");
                        asm volatile("st.async.weak.shared::cluster.mbarrier::complete_tx::bytes.v4.u32 [%0], {%1, %2, %3, %4}, [%5];"
                                     :: "r"(rtk + ((j & 7) << 4)), "r"(t.x | ((uint32_t)(j + 1) << 20)), "r"(t.y), "r"(t.z), "r"(t.w), "r"(rfull + 8 * s) : "memory");
                    }
                    if (++s == NSLOT) { s = 0; ph ^= 1; }
                };
                if (HELPER) {
#pragma unroll 1
                    for (int j = 0; j < XEARLY; j++) request(j, entry_w(p.ncl + cid + (j >> 1) * (p.ncl + p.nh), j & 1, j & 1, 0));
                    mbar_wait(sb + OFF_PLAN, 0);
                    mbar_wait(sb + OFF_GO, 0);
                    for (int j = XEARLY;; j++) {
                        const uint4 t = lds128v(sb + OFF_TAB + 16 * (j - XEARLY));
                        request(j, t);
                        if (__any_sync(~0u, t.x == NO_TILE)) break;
                    }
                } else {
                    static_assert(XEARLY == 2, "");
                    request(0, e0);
                    request(1, e1);
                    mbar_wait(sb + OFF_PLAN, 0);
                    const uint4 inf = lds128v(sb + OFF_INFO);
                    const unsigned long long plan = inf.x | ((unsigned long long)inf.y << 32);
                    const int side = inf.z & 1, nc = inf.z >> 16;
                    const int nh = helpers(p, plan, side), rm = p.rm[nh], rmo = p.rm[p.nh - nh];
                    const uint32_t ratio = p.ratio[nh], ratioo = p.ratio[p.nh - nh];
                    const int st = NSTAT * nc, sto = NSTAT * (p.ncl - nc);
                    uint4 t = lds128v(sb + OFF_TAB + 16 * ((inf.z >> 8) & 0xFF));
                    mbar_wait(sb + OFF_GO, 0);
                    int j = XEARLY;
#pragma unroll 1
                    for (; j < XEARLY + NSTAT - 2; j++) {
                        const uint4 tn = lds128v(sb + OFF_TAB + 16 * (((inf.z >> 8) & 0xFF) + (j + 1 - XEARLY) * nc));
                        request(j, t);
                        t = tn;
                    }
                    uint32_t drawn = 0;
                    int q = side;
                    request(j++, t);
                    draw(drawn, &g_ticket, 1u << (16 * side));
                    t = lds128v(sb + OFF_TAB + 16 * (((inf.z >> 8) & 0xFF) + (NSTAT - 1) * nc));
                    mbar_wait(sb + OFF_PLAN2, 0);
                    for (;; j++) {
                        request(j, t);
                        uint32_t v = __reduce_max_sync(~0u, drawn);
                        int m = st + ((v >> (16 * side)) & 0xFFFF), mo = sto + ((v >> (16 - 16 * side)) & 0xFFFF);
                        if (q == side ? m >= rm && mo < rmo : mo >= rmo && m < rm) {
                            q ^= 1;
                            draw(drawn, &g_ticket, 1u << (16 * q));
                            v = __reduce_max_sync(~0u, drawn);
                            m = st + ((v >> (16 * side)) & 0xFFFF); mo = sto + ((v >> (16 - 16 * side)) & 0xFFFF);
                        }
                        if (q == side ? m >= rm : mo >= rmo) break;
                        const bool own = q == side;
                        q = m + ((m * ratio) >> 16) > mo + ((mo * ratioo) >> 16) + DELTA ? side ^ 1 : side;
                        draw(drawn, &g_ticket, 1u << (16 * q));
                        if (own) t = lds128v(sb + OFF_TAB + 16 * m);
                        else t = cl_entry(p, mo, side ^ 1, ratioo, plan);
                    }
                    t.x = NO_TILE;
                    request(j + 1, t);
                    if (lane == 0 && atomicInc(&g_done, p.ncl - 1) == (uint32_t)p.ncl - 1) g_ticket = 0;
                }
            }
        } else {
            const int g = warp - 13;
            uint64_t spol;
            asm volatile("createpolicy.fractional.L2::evict_first.b64 %0, 1.0;" : "=l"(spol));
            mbar_wait(sb + OFF_GO, 0);
            if (g == 2 && lane == 0 && atomicInc(&g_passed, p.nctas - 1) == (uint32_t)p.nctas - 1) {
#pragma unroll
                for (int m = 0; m < 36; m++) g_ready[m * 32] = 0;
                g_plan = make_ulonglong2(0, 0);
            }
            __syncwarp();
            for (int i = 0;; i++) {
                asm volatile("bar.arrive %0, 160;" :: "r"(12 + g) : "memory");
                asm volatile("bar.sync %0, 160;" :: "r"(1 + g) : "memory");
                const uint4 t = lds128v(tk + ((i & 7) << 4));
                if ((t.x & NO_TILE) == NO_TILE) break;
                const CUtensorMap* tm = &maps.o[(t.x >> 14) & 1];
                const int row[4] = {(int)(t.y & 0xFFFF), (int)(t.y >> 16), (int)(t.z & 0xFFFF), (int)(t.z >> 16)};
                if (lane == 0) {
#pragma unroll
                    for (int k = 0; k < 4; k++)
                        asm volatile("cp.async.bulk.tensor.3d.global.shared::cta.bulk_group.L2::cache_hint [%0, {%2, %3, %4}], [%1], %5;"
                                     :: "l"(tm), "r"(sb + OFF_STG + (g + 3 * (i & 1)) * STG_BYTES + k * 1024), "r"((g * 3 + rank) * 64), "r"(row[k]), "r"(0), "l"(spol) : "memory");
                    asm volatile("cp.async.bulk.commit_group;" ::: "memory");
                    asm volatile("cp.async.bulk.wait_group.read 1;" ::: "memory");
                }
                __syncwarp();
            }
            if (lane == 0) asm volatile("cp.async.bulk.wait_group.read 0;" ::: "memory");
        }
        __syncwarp();
        if (!HELPER) asm volatile("barrier.cluster.arrive.relaxed.aligned;\nbarrier.cluster.wait.aligned;" ::: "memory");
    } else {
        asm volatile("setmaxnreg.inc.sync.aligned.u32 160;");
        const int wg = warp >> 2, wtid = tid & 127;
        if (HELPER) asm volatile("bar.sync 0;" ::: "memory");
        else {
            int prb = cid;
            if (prb >= 36) asm volatile("barrier.cluster.wait.aligned;" ::: "memory");
#pragma unroll 1
            for (int round = 0; prb < 36; prb += p.ncl, round++) {
                const uint32_t wsm = sb + OFF_WST, msk = sb + OFF_MSK + (round & 1) * 288, mbar = sb + OFF_MBAR + (round & 1) * 8;
                if (round) {
                    asm volatile("bar.sync 3, 384;" ::: "memory");
                    if (tid == 0) mbar_expect_tx(mbar, 36 * 8);
                    prep_load(prb >> 2);
                }
                const int nt = ties(wv[0].x, wv[1].x, wv[2].x, wv[3].x) + ties(wv[0].y, wv[1].y, wv[2].y, wv[3].y) +
                               ties(wv[0].z, wv[1].z, wv[2].z, wv[3].z) + ties(wv[0].w, wv[1].w, wv[2].w, wv[3].w);
                const uint32_t mk = __ballot_sync(~0u, nt > 0), md = __ballot_sync(~0u, nt > 1);
                if (round == 0) asm volatile("barrier.cluster.wait.aligned;" ::: "memory");
                if (lane < CL)
                    asm volatile("st.async.weak.shared::cluster.mbarrier::complete_tx::bytes.v2.u32 [%0], {%1, %2}, [%3];"
                                 :: "r"(mapa(msk + (rank * 12 + warp) * 8, lane)), "r"(mk), "r"(md), "r"(mapa(mbar, lane)) : "memory");
#pragma unroll
                for (int j = 0; j < 4; j++) {
                    const int row = wrow + j;
                    const uint32_t ad = wsm + row * 128 + (((lane >> 2) ^ ((row & 1) | ((row >> 1) & 6))) << 4);
                    asm volatile("st.shared.v4.b32 [%0], {%1,%2,%3,%4};" :: "r"(ad), "r"(wv[j].x), "r"(wv[j].y), "r"(wv[j].z), "r"(wv[j].w) : "memory");
                }
                if (warp == 0) {
                    mbar_wait(mbar, (round >> 1) & 1);
                    uint4 ms = make_uint4(0, 0, 0, 0);
                    if (lane < KSTEPS) ms = lds128v(msk + 16 * lane);
                    const uint32_t te = (ms.x & 0x0F0F0F0Fu) | ((ms.z & 0x0F0F0F0Fu) << 4), to = ((ms.x >> 4) & 0x0F0F0F0Fu) | (ms.z & 0xF0F0F0F0u);
                    const uint32_t de = (ms.y & 0x0F0F0F0Fu) | ((ms.w & 0x0F0F0F0Fu) << 4), dq = ((ms.y >> 4) & 0x0F0F0F0Fu) | (ms.w & 0xF0F0F0F0u);
                    auto count = [](uint32_t v) { v -= (v >> 1) & 0x55555555u; v = (v & 0x33333333u) + ((v >> 2) & 0x33333333u); return (v + (v >> 4)) & 0x0F0F0F0Fu; };
                    const uint32_t c0 = __reduce_add_sync(~0u, count(te)), c1 = __reduce_add_sync(~0u, count(to));
                    auto byte = [](uint32_t a, uint32_t b, uint32_t u) { return __byte_perm(a, b, (u >> 1) + 4 * (u & 1)) & 0xFFu; };
                    const uint32_t ku = byte(c0, c1, lane & 7) * 8 + (lane & 7), k2 = 2 * (lane >> 3);
                    const uint32_t ranks = __reduce_add_sync(~0u, ((byte(c0, c1, k2) * 8 + k2 < ku) + (byte(c0, c1, k2 + 1) * 8 + k2 + 1 < ku)) << (4 * (lane & 7)));
                    const uint32_t order = __reduce_add_sync(~0u, lane < 8 ? lane << (4 * ((ranks >> (4 * lane)) & 7)) : 0);
                    int cnt[4]; uint32_t mq = 0;
#pragma unroll
                    for (int z = 0; z < 4; z++) {
                        const uint32_t ua = (order >> (4 * z)) & 7, ub = (order >> (28 - 4 * z)) & 7;
                        const uint32_t ta = byte(te, to, ua), tb = byte(te, to, ub), v = ta | tb | ((ta & tb) | byte(de, dq, ua) | byte(de, dq, ub)) << 8;
                        cnt[z] = __popc(v);
                        if (z == (prb & 3)) mq = v;
                    }
                    const uint32_t l01 = __reduce_add_sync(~0u, cnt[0] | cnt[1] << 16), l23 = __reduce_add_sync(~0u, cnt[2] | cnt[3] << 16);
                    const int ulo = (order >> (4 * (prb & 3))) & 7, uhi = (order >> (28 - 4 * (prb & 3))) & 7;
                    const int full = max(max(max((int)(l01 & 0xFFFF) - cnt[0], (int)(l01 >> 16) - cnt[1]), max((int)(l23 & 0xFFFF) - cnt[2], (int)(l23 >> 16) - cnt[3])), 16);
                    const int twice = __reduce_min_sync(~0u, lane < KSTEPS ? full << 12 | (65 - cnt[0] - cnt[1] - cnt[2] - cnt[3]) << 5 | lane : full << 12 | 31) & 31;
                    sts32(sb + OFF_SEL + 4 * lane, lane == 31 ? ulo | (uhi << 4) | (twice << 8) : lane == twice ? 0 : mq);
                }
                asm volatile("bar.sync 1, 384;" ::: "memory");
                const uint32_t units = lds32v(sb + OFF_SEL + 4 * 31), mq = lds32v(sb + OFF_SEL + 4 * min(lane, 30));
                uint32_t wm[4];
                load_units(wsm, warp, units & 7, (units >> 4) & 7, lane, wm);
                emit_half(wm, mq, prb, rank * 6 + (warp >> 1), warp & 1, lane, units, b0, b1);
                asm volatile("bar.sync 2, 384;" ::: "memory");
                if (tid == 0) asm volatile("red.release.gpu.global.add.u32 [%0], 1;" :: "l"(&g_ready[prb * 32]) : "memory");
            }
            if (warp == 0 && lane < CL) mbar_arrive_cluster(mapa(sb + OFF_GO, lane));
        }
        const int mt = wg * 3 + rank, rb = mt * 4 + (warp & 3);
        {
            uint32_t v; int n = 0;
            do { asm volatile("ld.acquire.gpu.global.u32 %0, [%1];" : "=r"(v) : "l"(&g_ready[rb * 32]) : "memory"); fail_if(++n > (1 << 22)); } while (__any_sync(~0u, v < CL));
        }
        if (wg > 0) asm volatile("bar.sync %0, 256;" :: "r"(7 + wg) : "memory");
        uint32_t a[KSTEPS + 1][4], meta[9];
        uint2 rv[3]; uint32_t ro[3], sel[3];
        uint32_t info, bias_lo, bias_hi;
        {
            const uint4* ap = g_aux + rb * 6 * 32 + lane;
            const uint4 v3 = ldw(ap + 96), v2 = ldw(ap + 64), v4 = ldw(ap + 128), v5 = ldw(ap + 160), v0 = ldw(ap), v1 = ldw(ap + 32);
            meta[0] = v0.x; meta[1] = v0.y; meta[2] = v0.z; meta[3] = v0.w; meta[4] = v1.x; meta[5] = v1.y; meta[6] = v1.z; meta[7] = v1.w;
            meta[8] = v2.x; info = v2.y; bias_lo = v2.z; bias_hi = v2.w;
            ro[0] = v3.x; ro[1] = v3.y; ro[2] = v3.z;
            rv[0] = make_uint2(v4.x, v4.y); rv[1] = make_uint2(v4.z, v4.w); rv[2] = make_uint2(v5.x, v5.y);
        }
#pragma unroll
        for (int k = 0; k < KSTEPS + 1; k++) { uint4 v = ldw(&g_afrag[(mt * (KSTEPS + 1) + k) * 128 + wtid]); a[k][0] = v.x; a[k][1] = v.y; a[k][2] = v.z; a[k][3] = v.w; }
        if (wg < 2) asm volatile("bar.arrive %0, 256;" :: "r"(8 + wg) : "memory");
        if (lane == 0) mbar_arrive(sb + OFF_GO);
        auto selector = [](uint32_t o) { return 0x5410u + ((o >> 15) & 1) * 0x22u + (o >> 31) * 0x2200u; };
#pragma unroll
        for (int j = 0; j < 3; j++) { sel[j] = selector(ro[j]); ro[j] &= 0x7FFF7FFFu; }
        mbar_wait(bar_full, 0);
        info = __shfl_sync(~0u, info, 0);
        const int ngrp = info & 0xFF, ulo = (info >> 8) & 7, uhi = (info >> 12) & 7;
        const uint32_t stg = sb + OFF_STG + wg * STG_BYTES + ((lane >> 4) * 8 + (lane & 7)) * 128 + (((((lane >> 3) & 1) ? uhi : ulo) ^ (lane & 7)) << 4);
        const uint32_t twice = (((info >> 17) & 15) * 1024 + ((info >> 16) & 1) * 64) >> 4;
        const uint32_t rempty = HELPER ? bar_empty : mapa(bar_empty, 0);
        float acc[NACC];
        uint32_t bq[NB][6];
        auto gather = [&](uint32_t xb) {
#pragma unroll
            for (int j = 0; j < 4; j++) {
                const uint32_t o = xb + ((j & 1) ? ro[j >> 1] >> 16 : ro[j >> 1] & 0xFFFF);
#pragma unroll
                for (int n = 0; n < NB; n++) {
                    if (j < 3) { bq[n][j] = lds32(o + n * 9216); continue; }
                    bq[n][j] = 0;
                    asm volatile("{\n.reg .pred p;\nsetp.lt.s32 p, %2, %3;\n@p ld.shared.b32 %0, [%1];\n}" : "+r"(bq[n][j]) : "r"(o + n * 9216), "r"(j), "r"(ngrp) : "memory");
                }
            }
        };
        auto select = [&]() {
#pragma unroll
            for (int n = 0; n < NB; n++)
#pragma unroll
                for (int j = 0; j < 2; j++) bq[n][2 * j] = __byte_perm(bq[n][2 * j], bq[n][2 * j + 1], sel[j]);
        };
        auto further = [&](uint32_t xb, int bar) {
#pragma unroll 1
            for (int y = 4; y < min(ngrp, 5); y++) {
#pragma unroll
                for (int n = 0; n < NB; n++) { bq[n][4] = lds32(xb + (ro[2] & 0xFFFF) + n * 9216); bq[n][5] = lds32(xb + (ro[2] >> 16) + n * 9216); }
#pragma unroll
                for (int n = 0; n < NB; n++) mma_k8(acc + 4 * n, rv[2], __byte_perm(bq[n][4], bq[n][5], sel[2]));
                if (bar >= 0) asm volatile("bar.arrive %0, 256;" :: "r"(bar) : "memory");
#pragma unroll 1
                for (int z = 3; 2 * z < ngrp; z++) {
                    const uint2 v = __ldca(&g_rval[(rb * 36 + z) * 32 + lane]); const uint32_t off = __ldca(&g_roff[(rb * 36 + z) * 32 + lane]);
                    uint32_t bx[NB];
#pragma unroll
                    for (int n = 0; n < NB; n++) bx[n] = __byte_perm(lds32(xb + (off & 0x7FFF) + n * 9216), lds32(xb + ((off >> 16) & 0x7FFF) + n * 9216), selector(off));
#pragma unroll
                    for (int n = 0; n < NB; n++) mma_k8(acc + 4 * n, v, bx[n]);
                }
            }
        };
        bool more = true;
#pragma unroll
        for (int n = 0; n < NB; n++) bq[n][4] = bq[n][5] = 0;
        gather(sb + OFF_X);
        select();
#pragma unroll
        for (int n = 0; n < NB; n++) mma_k16(acc + 4 * n, rv[0], rv[1], bq[n][0], bq[n][2], 0.f, 0.f, 0.f, 0.f);
        further(sb + OFF_X, -1);
        const int bar_a = 8 + wg, bar_an = 8 + (wg + 2) % 3, bar_tn = 4 + (wg + 2) % 3;
        if (wg == 1) asm volatile("bar.arrive 4, 256;" ::: "memory");
        if (wg == 2) { asm volatile("bar.sync 10, 256;" ::: "memory"); asm volatile("bar.arrive 5, 256;" ::: "memory"); }
        auto run = [&](auto tw) {
        constexpr bool TW = decltype(tw)::value;
        int s = 0; uint32_t ph = 0;
        bool ready = false;
        for (int i = 0; more; i++) {
            const uint32_t xb = sb + OFF_X + s * TILE_BYTES;
            const int s1 = s + 1 == NSLOT ? 0 : s + 1;
            const uint32_t ph1 = s1 == 0 ? ph ^ 1 : ph;
            asm volatile("bar.sync %0, 256;" :: "r"(4 + wg) : "memory");
            const uint64_t desc = ((uint64_t)1 << 62) | ((uint64_t)(9216 >> 4) << 32) | ((uint64_t)1 << 16) | (uint64_t)(xb >> 4);
            asm volatile("wgmma.fence.sync.aligned;" ::: "memory");
#pragma unroll
            for (int k = 0; k < KSTEPS; k++) {
                const uint64_t d = desc + (uint64_t)(((k >> 1) * 1024 + (k & 1) * 64) >> 4);
                if (k & 1) wgmma_sp<1>(acc, a[k], d, meta[k >> 1]);
                else       wgmma_sp<0>(acc, a[k], d, meta[k >> 1]);
            }
            if (TW) wgmma_sp<0>(acc, a[KSTEPS], desc + twice, 0x44444444u);
            asm volatile("wgmma.commit_group.sync.aligned;" ::: "memory");
            asm volatile("bar.arrive %0, 256;" :: "r"(bar_an) : "memory");
            if (!ready) mbar_wait(bar_full + 8 * s1, ph1);
            const uint32_t tn = lds32v(tk + (((i + 1) & 7) << 4));
            gather(sb + OFF_X + s1 * TILE_BYTES);
            asm volatile("bar.sync %0, 160;" :: "r"(12 + wg) : "memory");
            asm volatile("wgmma.wait_group.sync.aligned 0;" ::: "memory");
            const uint32_t sg = stg + (i & 1) * (3 * STG_BYTES);
            if (wtid == 0) { if (HELPER) mbar_arrive(bar_empty + 8 * s); else mbar_arrive_cluster(rempty + 8 * s); }
#pragma unroll
            for (int n = 0; n < NB; n += 2) {
                const uint32_t p0 = pack_bias(acc[4 * n], acc[4 * n + 1], bias_lo), p1 = pack_bias(acc[4 * n + 2], acc[4 * n + 3], bias_hi);
                const uint32_t p2 = pack_bias(acc[4 * n + 4], acc[4 * n + 5], bias_lo), p3 = pack_bias(acc[4 * n + 6], acc[4 * n + 7], bias_hi);
                if (n == 0) asm volatile("stmatrix.sync.aligned.m8n8.x4.trans.shared.b16 [%0], {%1,%2,%3,%4};" :: "r"(sg + n * 1024), "r"(p0), "r"(p1), "r"(p2), "r"(p3) : "memory");
                else asm volatile("{\n.reg .pred p;\nAGAIN:\nstmatrix.sync.aligned.m8n8.x4.trans.shared.b16 [%0], {%1,%2,%3,%4};\nsetp.eq.u32 p, %5, 0xFFFFFFFE;\n@p bra.uni AGAIN;\n}"
                                  :: "r"(sg + n * 1024), "r"(p0), "r"(p1), "r"(p2), "r"(p3), "r"(info) : "memory");
            }
            more = __any_sync(~0u, (tn & NO_TILE) != NO_TILE);
            select();
            if (wg != 2 || more) {
                asm volatile("{\n.reg .pred p;\nTURN:\nbar.sync %0, 256;\nsetp.eq.u32 p, %1, 0xFFFFFFFF;\n@p bra.uni TURN;\n}" :: "r"(bar_a), "r"(info) : "memory");
#pragma unroll
                for (int n = 0; n < NB; n++) {
                    mma_k16(acc + 4 * n, rv[0], rv[1], bq[n][0], bq[n][2], 0.f, 0.f, 0.f, 0.f);
                    if (n == 0) asm volatile("{\n.reg .pred p;\nsetp.le.s32 p, %1, 4;\n@p bar.arrive %0, 256;\n}" :: "r"(bar_tn), "r"(ngrp) : "memory");
                }
                further(sb + OFF_X + s1 * TILE_BYTES, bar_tn);
            }
            asm volatile("fence.proxy.async.shared::cta;" ::: "memory");
            asm volatile("bar.arrive %0, 160;" :: "r"(1 + wg) : "memory");
            s = s1; ph = ph1;
            ready = __all_sync(~0u, mbar_test(bar_full + 8 * (s + 1 == NSLOT ? 0 : s + 1), s + 1 == NSLOT ? ph ^ 1 : ph));
        }
        };
        if (((info >> 16) & 31) < KSTEPS) run(Flag<true>()); else run(Flag<false>());
        if (wg == 0) asm volatile("bar.sync 4, 256;" ::: "memory");
        asm volatile("bar.sync %0, 160;" :: "r"(12 + wg) : "memory");
        asm volatile("bar.arrive %0, 160;" :: "r"(1 + wg) : "memory");
        if (!HELPER) asm volatile("barrier.cluster.arrive.relaxed.aligned;\nbarrier.cluster.wait.aligned;" ::: "memory");
    }
}

typedef CUresult (*EncodeFn)(CUtensorMap*, CUtensorMapDataType, cuuint32_t, void*, const cuuint64_t*, const cuuint64_t*, const cuuint32_t*, const cuuint32_t*,
                             CUtensorMapInterleave, CUtensorMapSwizzle, CUtensorMapL2promotion, CUtensorMapFloatOOBfill);

__global__ void plain_kernel(const __nv_bfloat16* x, const __nv_bfloat16* w, const __nv_bfloat16* b, __nv_bfloat16* out, int ntok) {
    const int t0 = blockIdx.x * 8;
    for (int f = threadIdx.x; f < D; f += blockDim.x) {
        float acc[8] = {};
        for (int g = 0; g < D / 4; g++) {
            float v[4], m[4];
            for (int i = 0; i < 4; i++) { v[i] = __bfloat162float(w[(4 * g + i) * D + f]); m[i] = fabsf(v[i]); }
            const float thr = fmaxf(fminf(fmaxf(m[0], m[1]), fmaxf(m[2], m[3])), fmaxf(fminf(m[0], m[1]), fminf(m[2], m[3])));
            for (int i = 0; i < 4; i++)
                for (int t = 0; t < 8; t++)
                    if (m[i] >= thr && t0 + t < ntok) acc[t] += v[i] * __bfloat162float(x[(size_t)(t0 + t) * D + 4 * g + i]);
        }
        for (int t = 0; t < 8; t++)
            if (t0 + t < ntok) out[(size_t)(t0 + t) * D + f] = __hadd(__float2bfloat16(acc[t]), b[f]);
    }
}

extern "C" void kernel_launch(void* const* d_in, const int* in_sizes, int n_in, void* d_out, int out_size) {
    static EncodeFn enc = nullptr;
    static int ncl = 0, nhelp = 0;
    const int ntok = in_sizes[0] / D;
    cudaLaunchConfig_t cfg = {};
    cudaLaunchAttribute at[1];
    at[0].id = cudaLaunchAttributeClusterDimension; at[0].val.clusterDim.x = CL; at[0].val.clusterDim.y = 1; at[0].val.clusterDim.z = 1;
    cfg.blockDim = dim3(NTHREADS); cfg.dynamicSmemBytes = SMEM_BYTES; cfg.attrs = at; cfg.numAttrs = 1; cfg.stream = cudaStreamPerThread;
    if (!enc) {
        cudaDriverEntryPointQueryResult qr; void* fn = nullptr;
        cudaGetDriverEntryPoint("cuTensorMapEncodeTiled", &fn, cudaEnableDefault, &qr);
        enc = (EncodeFn)fn;
        cudaFuncSetAttribute(spgemm_kernel<false>, cudaFuncAttributeMaxDynamicSharedMemorySize, SMEM_BYTES);
        cudaFuncSetAttribute(spgemm_kernel<true>, cudaFuncAttributeMaxDynamicSharedMemorySize, SMEM_BYTES);
        int dev = 0, nsm = 0;
        cudaGetDevice(&dev);
        cudaDeviceGetAttribute(&nsm, cudaDevAttrMultiProcessorCount, dev);
        cfg.gridDim = dim3(CL * (nsm / CL));
        cudaOccupancyMaxActiveClusters(&ncl, spgemm_kernel<false>, &cfg);
        if (ncl < 1) ncl = 1;
        nhelp = nsm > CL * ncl ? (nsm - CL * ncl) / CL : 0;
        if (nhelp > 7) nhelp = 7;
    }
    if (ntok % 4096 || ntok < 16384 || ntok > 65536 || ncl < 2 || ncl > 56 || ncl < CL * nhelp || 8 * (ncl + nhelp) > ntok / 64) {
        plain_kernel<<<(ntok + 7) / 8, 192, 0, cudaStreamPerThread>>>((const __nv_bfloat16*)d_in[0], (const __nv_bfloat16*)d_in[1], (const __nv_bfloat16*)d_in[2], (__nv_bfloat16*)d_out, ntok);
        return;
    }
    Maps maps;
    for (int v = 0; v < 2; v++) {
        const cuuint32_t rows = v == 0 ? 2 : 1;
        const cuuint64_t pitch = (v == 0 ? 14 : 57) * D * 2;
        {
            cuuint64_t dims[4] = {64, (cuuint64_t)ntok, 8 / rows, 9};
            cuuint64_t strides[3] = {D * 2, pitch, 128};
            cuuint32_t box[4] = {64, rows, 8 / rows, 9}, es[4] = {1, 1, 1, 1};
            enc(&maps.x[v], CU_TENSOR_MAP_DATA_TYPE_BFLOAT16, 4, d_in[0], dims, strides, box, es, CU_TENSOR_MAP_INTERLEAVE_NONE,
                CU_TENSOR_MAP_SWIZZLE_128B, CU_TENSOR_MAP_L2_PROMOTION_L2_128B, CU_TENSOR_MAP_FLOAT_OOB_FILL_NONE);
        }
        {
            cuuint64_t dims[3] = {D, (cuuint64_t)ntok, 8 / rows};
            cuuint64_t strides[2] = {D * 2, pitch};
            cuuint32_t box[3] = {64, rows, 8 / rows}, es[3] = {1, 1, 1};
            enc(&maps.o[v], CU_TENSOR_MAP_DATA_TYPE_BFLOAT16, 3, d_out, dims, strides, box, es, CU_TENSOR_MAP_INTERLEAVE_NONE,
                CU_TENSOR_MAP_SWIZZLE_128B, CU_TENSOR_MAP_L2_PROMOTION_NONE, CU_TENSOR_MAP_FLOAT_OOB_FILL_NONE);
        }
    }
    {
        cuuint64_t dims[3] = {256, (cuuint64_t)ntok * D * 2 / 2048, 4};
        cuuint64_t strides[2] = {2048, 16384};
        cuuint32_t box[3] = {256, 4, 4}, es[3] = {1, 1, 1};
        enc(&maps.pf, CU_TENSOR_MAP_DATA_TYPE_FLOAT64, 3, d_in[0], dims, strides, box, es, CU_TENSOR_MAP_INTERLEAVE_NONE,
            CU_TENSOR_MAP_SWIZZLE_NONE, CU_TENSOR_MAP_L2_PROMOTION_NONE, CU_TENSOR_MAP_FLOAT_OOB_FILL_NONE);
    }
    Params p;
    p.w = (const uint16_t*)d_in[1]; p.bias = (const uint16_t*)d_in[2]; p.x = (const uint8_t*)d_in[0];
    p.nq = ntok / 64; p.npages = (int)(((size_t)ntok * D * 2) >> 21);
    const int nc = ncl, nh = nhelp;
    p.ncl = nc; p.nh = nh; p.nctas = CL * (nc + nh);
    p.m0 = (nc + nh) * XEARLY / 2;
    for (int h = 0; h < 8; h++) {
        const uint32_t R = p.nq - p.m0, H = h * (HT * p.nq / 1024 * 44 / (nc + nh));
        p.ratio[h] = h <= nh ? (H << 16) / (R - H) : 0;
        p.rm[h] = p.ratio[h] ? (((R - 1) << 16) + 0x7FFFu) / (0x10000u + p.ratio[h]) + 1 : R;
    }
    p.c0 = (p.m0 * 9) >> 3;
    p.tb = p.m0 + (NSLOT - XEARLY) * (nc + nh) / 2;
    p.ta = p.tb + 1 + (int)((p.nq - p.tb) * TAFRAC); p.te = (int)(p.nq * TEFRAC) + 2;
    p.slope0 = ((LEAD1 - LEAD0) << 16) / (p.ta - p.tb); p.slope1 = ((LEAD1 - LEADE) << 16) / (p.te - p.ta);
    cfg.gridDim = dim3(CL * nc);
    cudaLaunchKernelEx(&cfg, spgemm_kernel<false>, p, maps);
    if (nh) {
        at[0].id = cudaLaunchAttributeProgrammaticStreamSerialization; at[0].val.programmaticStreamSerializationAllowed = 1;
        cfg.gridDim = dim3(CL * nh);
        cudaLaunchKernelEx(&cfg, spgemm_kernel<true>, p, maps);
    }
}
```

```cpp
#include <cuda_runtime.h>
#include <cuda_bf16.h>
#include <cuda.h>
#include <stdint.h>

constexpr int D = 576;
constexpr int NT = 32;
constexpr int NSLOT = 5;
constexpr int XEARLY = 2;
constexpr int NSTAT = 4;
constexpr int DELTA = 36;
constexpr int HT = 45;
constexpr int LEAD0 = 140, LEAD1 = 295, LEADE = 27, PACE = 1200;
constexpr double TAFRAC = 0.261, TEFRAC = 1.0;
constexpr int PWAIT = 1900;
constexpr int KSTEPS = 18;
constexpr int CL = 3;
constexpr int TILE_BYTES = NT * D * 2;
constexpr int STG_BYTES = NT * 128;
constexpr int NACC = NT / 2;
constexpr int NB = NT / 8;
constexpr int NCONS = 384;
constexpr int NTHREADS = 512;
constexpr int NTAB = 1024;
constexpr uint32_t NO_TILE = 0xFFFFFu;

constexpr int OFF_X = 0;
constexpr int OFF_WST = OFF_X + (NSLOT - 1) * TILE_BYTES;
constexpr int OFF_STG = OFF_X + NSLOT * TILE_BYTES;
constexpr int OFF_TAB = OFF_STG + 6 * STG_BYTES;
constexpr int OFF_TK = OFF_TAB + 16 * NTAB;
constexpr int OFF_MSK = OFF_TK + 128;
constexpr int OFF_SEL = OFF_MSK + 2 * 36 * 8;
constexpr int OFF_INFO = OFF_SEL + 128;
constexpr int OFF_FULL = OFF_INFO + 32;
constexpr int OFF_EMPTY = OFF_FULL + 8 * NSLOT;
constexpr int OFF_MBAR = OFF_EMPTY + 8 * NSLOT;
constexpr int OFF_GO = OFF_MBAR + 16;
constexpr int OFF_PLAN = OFF_GO + 8;
constexpr int OFF_PLAN2 = OFF_PLAN + 8;
constexpr int SMEM_BYTES = OFF_PLAN2 + 8 + 1024;
static_assert(SMEM_BYTES <= 232448 && TILE_BYTES >= 192 * 128 && XEARLY % 2 == 0 && XEARLY < NSLOT && NSLOT < 8 && NB == 4 && OFF_INFO % 16 == 0, "layout");

__device__ __align__(128) uint4    g_afrag[9 * (KSTEPS + 1) * 128];
__device__ __align__(128) uint4    g_aux[36 * 6 * 32];
__device__ __align__(128) uint2    g_rval[36 * 36 * 32];
__device__ __align__(128) uint32_t g_roff[36 * 36 * 32];
__device__ __align__(128) uint32_t g_ready[36 * 32];
__device__ __align__(128) uint32_t g_passed;
__device__ __align__(128) uint32_t g_ticket;
__device__ __align__(128) uint32_t g_hreg[3 * 32];
__device__ __align__(128) uint32_t g_done;
__device__ __align__(128) ulonglong2 g_plan;

__device__ __forceinline__ uint32_t max2(uint32_t a, uint32_t b) { uint32_t d; asm("max.u16x2 %0, %1, %2;" : "=r"(d) : "r"(a), "r"(b)); return d; }
__device__ __forceinline__ uint32_t min2(uint32_t a, uint32_t b) { uint32_t d; asm("min.u16x2 %0, %1, %2;" : "=r"(d) : "r"(a), "r"(b)); return d; }
__device__ __forceinline__ uint32_t sign2(uint32_t a) { uint32_t d; asm("prmt.b32 %0, %1, %1, 0xBB99;" : "=r"(d) : "r"(a)); return d; }
__device__ __forceinline__ void load_units(uint32_t wsm, int g4, int ulo, int uhi, int lane, uint32_t (&m)[4]) {
    const int row = g4 * 16 + ((lane & 7) >> 1) * 4 + ((lane >> 3) & 1) * 2 + (lane & 1);
    const uint32_t ad = wsm + row * 128 + (((lane < 16 ? ulo : uhi) ^ ((row & 1) | ((row >> 1) & 6))) << 4);
    asm volatile("ldmatrix.sync.aligned.m8n8.x4.trans.shared.b16 {%0,%1,%2,%3}, [%4];" : "=r"(m[0]), "=r"(m[1]), "=r"(m[2]), "=r"(m[3]) : "r"(ad) : "memory");
}
__device__ __forceinline__ void zip4(uint32_t a01, uint32_t a23, uint32_t b01, uint32_t b23, uint32_t (&x)[4]) {
    x[0] = __byte_perm(a01, b01, 0x5410); x[1] = __byte_perm(a01, b01, 0x7632); x[2] = __byte_perm(a23, b23, 0x5410); x[3] = __byte_perm(a23, b23, 0x7632);
}
__device__ __forceinline__ void middle2(const uint32_t (&x)[4], uint32_t (&m)[4], uint32_t& u, uint32_t& v) {
#pragma unroll
    for (int i = 0; i < 4; i++) m[i] = x[i] & 0x7FFF7FFFu;
    u = min2(max2(m[0], m[1]), max2(m[2], m[3])); v = max2(min2(m[0], m[1]), min2(m[2], m[3]));
}
__device__ __forceinline__ int ties(uint32_t x0, uint32_t x1, uint32_t x2, uint32_t x3) {
    const uint32_t x[4] = {x0, x1, x2, x3};
    uint32_t m[4], u, v;
    middle2(x, m, u, v);
    const uint32_t t = u ^ v, f = u ^ min2(min2(m[0], m[1]), min2(m[2], m[3]));
    const bool t0 = (t & 0xFFFFu) == 0 && (v & 0xFFFFu) != 0, t1 = t < 0x10000u && v >= 0x10000u;
    return t0 + t1 + 2 * ((t0 && (f & 0xFFFFu) == 0) || (t1 && f < 0x10000u));
}
__device__ __forceinline__ void split(const uint32_t (&x)[4], bool dbl, bool P, uint32_t& alo, uint32_t& ahi, uint32_t& nib, uint32_t& va, uint32_t& vb) {
    uint32_t m[4], u, v;
    middle2(x, m, u, v);
    const uint32_t c = 0x80008000u - max2(max2(u, v), 0x00010001u);
    uint32_t k0 = sign2(m[0] + c), k1 = sign2(m[1] + c), k2 = sign2(m[2] + c), k3 = sign2(m[3] + c);
    const uint32_t three = (k0 & k1 & (k2 | k3)) | (k2 & k3 & (k0 | k1)), four = k0 & k1 & k2 & k3;
    const bool a2 = !dbl && P;
    const uint32_t pa = a2 ? k2 : k0, pb = dbl ? k2 : P ? k3 : k1;
    const uint32_t ra = three & pa, rb = three & pb & (four | ~pa);
    va = (a2 ? x[2] : x[0]) & ra; vb = (dbl ? x[2] : P ? x[3] : x[1]) & rb;
    if (a2) k2 &= ~ra; else k0 &= ~ra;
    if (dbl) k2 &= ~rb; else if (P) k3 &= ~rb; else k1 &= ~rb;
    const uint32_t s1 = k1 & k0, s2 = k2 & (k0 | k1);
    const uint32_t t = (k1 & x[1]) | (~k1 & k2 & x[2]);
    const uint32_t x0 = (k0 & x[0]) | (~k0 & t), x1 = (s1 & x[1]) | (s2 & x[2]) | (k3 & x[3]);
    nib = (~k0 & k1 & 0x00010001u) | (~k0 & ~k1 & 0x00020002u) | (~s2 & 0x00040004u) | (~s1 & 0x00080008u);
    alo = __byte_perm(x0, x1, 0x5410); ahi = __byte_perm(x0, x1, 0x7632);
}
__device__ __forceinline__ uint32_t resid_off(int g, int P, int r) {
    int k0 = 4 * g + 2 * P;
    int chunk = k0 >> 6, byte = (k0 & 63) * 2;
    return chunk * 1024 + r * 128 + (((byte >> 4) ^ r) << 4) + (byte & 15);
}
__device__ __forceinline__ void emit_half(const uint32_t (&wm)[4], uint32_t md, int rb, int ks, int e, int lane, uint32_t units, uint32_t b0, uint32_t b1) {
    uint32_t* const aux = (uint32_t*)(g_aux + rb * 6 * 32);
    auto put_slot = [&](int j, int ln, uint32_t v, uint32_t off) {
        uint16_t* o = j < 6 ? (uint16_t*)aux + (3 * 32 + ln) * 8 + j : (uint16_t*)g_roff + ((rb * 36 + (j >> 1)) * 32 + ln) * 2 + (j & 1);
        uint16_t* w = j < 6 ? (uint16_t*)aux + ((4 + (j >> 2)) * 32 + ln) * 8 + (j & 2) * 2 + (j & 1) : (uint16_t*)g_rval + ((rb * 36 + (j >> 1)) * 32 + ln) * 4 + (j & 1);
        o[0] = (uint16_t)off; w[0] = (uint16_t)v; w[2] = (uint16_t)(v >> 16);
    };
    const int r = lane >> 2, q = lane & 3, g = 4 * e + q, twice = units >> 8;
    const uint32_t gm = __shfl_sync(~0u, md, ks);
    const uint32_t c2 = __popc(md & 0x5555u) | (__popc(md & 0xAAAAu) << 16);
    const uint32_t tot = __reduce_add_sync(~0u, c2), pre = __reduce_add_sync(~0u, lane < ks ? c2 : 0u);
    const int ne = tot & 0xFFFF, no = tot >> 16;
    const int rk = ((q & 1) ? pre >> 16 : pre & 0xFFFF) + __popc(gm & ((q & 1) ? 0xAAAAu : 0x5555u) & (((1u << g) - 1) * 0x101u));
    const bool dbl = (gm >> (8 + g)) & 1;
    uint32_t a0, a1, va, vb, x[4], nib;
    zip4(wm[0], wm[1], wm[2], wm[3], x); split(x, dbl, rk & 1 && ks != twice, a0, a1, nib, va, vb);
    uint2* const frag = (uint2*)(g_afrag + (rb >> 2) * (KSTEPS + 1) * 128 + (rb & 3) * 32 + lane) + e;
    frag[ks * 256] = make_uint2(a0, a1);
    if (ks == (twice < KSTEPS ? twice : 0)) frag[KSTEPS * 256] = twice < KSTEPS ? make_uint2(__byte_perm(va, vb, 0x5410), __byte_perm(va, vb, 0x7632)) : make_uint2(0, 0);
    nib <<= 4 * q;
    nib |= __shfl_xor_sync(~0u, nib, 1);
    nib |= __shfl_xor_sync(~0u, nib, 2);
    if (q == 2 * (ks & 1) + e) aux[((ks >> 3) * 32 + lane) * 4 + ((ks >> 1) & 3)] = nib;
    const int em = min(ne, max(8, 16 - no)), om = min(no, 16 - em);
    const int odd = q & 1, m = odd ? om : em;
    auto place = [&](int k) {
        const int t = 15 - k;
        return k >= m ? 16 + (odd ? ne - em : 0) + k - m : k < 8 ? (k >> 1) * 4 + 2 * odd + (k & 1) : (t >> 1) * 4 + 2 * (odd ^ 1) + (t & 1);
    };
    const uint32_t second = (__ballot_sync(~0u, vb != 0) & (0x11111111u << q)) != 0 && !dbl;
    if ((gm >> g) & 1) {
        const int sl = place(rk);
        put_slot(sl >> 2, r * 4 + (sl & 3), !dbl ? va | vb : (rk & 1) ? vb : va, resid_off(ks * 8 + g, rk & 1, r) | (second << 15));
        if (dbl) { const int s2 = place(rk + 1); put_slot(s2 >> 2, r * 4 + (s2 & 3), (rk & 1) ? va : vb, resid_off(ks * 8 + g, ~rk & 1, r)); }
    }
    const int ntot = ne + no, z = 2 * ks + e;
    const int ng = ntot > 16 ? (ntot + 3) >> 2 : min(4, (max(ne, no) + 1) >> 1);
    if (z == 8) {
        const int ulo = units & 7, uhi = (units >> 4) & 7;
        aux[(2 * 32 + lane) * 4 + 1] = ng | (units << 8);
        *(uint2*)(aux + (2 * 32 + lane) * 4 + 2) = make_uint2(__shfl_sync(~0u, ulo < 4 ? b0 : b1, (ulo * 8 + r) & 31) * 0x10001u, __shfl_sync(~0u, uhi < 4 ? b0 : b1, (uhi * 8 + r) & 31) * 0x10001u);
        aux[(3 * 32 + lane) * 4 + 3] = 0; *(uint2*)(aux + (5 * 32 + lane) * 4 + 2) = make_uint2(0, 0);
    }
    const int idx = 2 * z + (q & 1);
    const int frow = z < 6 ? z : z == 6 ? ng - 1 : ng;
    const bool fill = z < 4 ? !(idx < ((q >> 1) ? om : em) || (15 - idx) < ((q >> 1) ? em : om))
                            : (z < 6 || (ng > 6 && (z == 6 || (z == 7 && (ng & 1))))) && 4 * frow + q >= ntot;
    if (fill) put_slot(frow, lane, 0, resid_off(q >> 1, q & 1, r));
}

template<int SEL> __device__ __forceinline__ void wgmma_sp(float (&d)[NACC], const uint32_t (&a)[4], uint64_t bdesc, uint32_t meta) {
    asm volatile("{\n.reg .pred p;\nsetp.ne.b32 p, %22, 0;\n"
        "wgmma.mma_async.sp.sync.aligned.m64n32k32.f32.bf16.bf16 {%0, %1, %2, %3, %4, %5, %6, %7, %8, %9, %10, %11, %12, %13, %14, %15}, {%16, %17, %18, %19}, %20, %21, %23, p, 1, 1, 0;\n}\n"
        : "+f"(d[0]), "+f"(d[1]), "+f"(d[2]), "+f"(d[3]), "+f"(d[4]), "+f"(d[5]), "+f"(d[6]), "+f"(d[7]), "+f"(d[8]), "+f"(d[9]), "+f"(d[10]), "+f"(d[11]), "+f"(d[12]), "+f"(d[13]), "+f"(d[14]), "+f"(d[15])
        : "r"(a[0]), "r"(a[1]), "r"(a[2]), "r"(a[3]), "l"(bdesc), "r"(meta), "r"(1), "n"(SEL));
}

__device__ __forceinline__ void mbar_init(uint32_t bar, uint32_t cnt) { asm volatile("mbarrier.init.shared::cta.b64 [%0], %1;" :: "r"(bar), "r"(cnt) : "memory"); }
__device__ __forceinline__ void mbar_expect_tx(uint32_t bar, uint32_t bytes) {
    asm volatile("mbarrier.arrive.expect_tx.shared::cta.b64 _, [%0], %1;" :: "r"(bar), "r"(bytes) : "memory");
}
__device__ __forceinline__ void mbar_arrive(uint32_t bar) { asm volatile("mbarrier.arrive.shared::cta.b64 _, [%0];" :: "r"(bar) : "memory"); }
__device__ __forceinline__ void mbar_arrive_cluster(uint32_t bar) { asm volatile("mbarrier.arrive.shared::cluster.b64 _, [%0];" :: "r"(bar) : "memory"); }
__device__ __forceinline__ bool mbar_try(uint32_t bar, uint32_t parity) {
    uint32_t ok;
    asm volatile("{\n.reg .pred p;\nmbarrier.try_wait.parity.shared::cta.b64 p, [%1], %2;\nselp.u32 %0, 1, 0, p;\n}\n" : "=r"(ok) : "r"(bar), "r"(parity) : "memory");
    return ok;
}
__device__ __forceinline__ bool mbar_test(uint32_t bar, uint32_t parity) {
    uint32_t ok;
    asm volatile("{\n.reg .pred p;\nmbarrier.test_wait.parity.shared::cta.b64 p, [%1], %2;\nselp.u32 %0, 1, 0, p;\n}\n" : "=r"(ok) : "r"(bar), "r"(parity) : "memory");
    return ok;
}
__device__ __forceinline__ void fail_if(bool c) { asm volatile("{\n.reg .pred p;\nsetp.ne.u32 p, %0, 0;\n@p st.volatile.global.u32 [%1], %0;\n}\n" :: "r"((uint32_t)c), "l"(0ull) : "memory"); }
__device__ __forceinline__ void mbar_wait(uint32_t bar, uint32_t parity) {
    int n = 0;
    while (!mbar_try(bar, parity)) fail_if(++n > (1 << 20));
}
__device__ __forceinline__ void st_async(uint32_t addr, uint32_t v, uint32_t bar) {
    asm volatile("st.async.weak.shared::cluster.mbarrier::complete_tx::bytes.u32 [%0], %1, [%2];" :: "r"(addr), "r"(v), "r"(bar) : "memory");
}
__device__ __forceinline__ uint32_t mapa(uint32_t a, uint32_t cta) { uint32_t d; asm("mapa.shared::cluster.u32 %0, %1, %2;" : "=r"(d) : "r"(a), "r"(cta)); return d; }
__device__ __forceinline__ uint32_t lds32(uint32_t a) { uint32_t v; asm volatile("ld.shared.b32 %0, [%1];" : "=r"(v) : "r"(a)); return v; }
__device__ __forceinline__ uint32_t lds32v(uint32_t a) { uint32_t v; asm volatile("ld.volatile.shared.b32 %0, [%1];" : "=r"(v) : "r"(a) : "memory"); return v; }
__device__ __forceinline__ void sts32(uint32_t a, uint32_t v) { asm volatile("st.shared.b32 [%0], %1;" :: "r"(a), "r"(v) : "memory"); }
__device__ __forceinline__ uint4 ldw(const uint4* a) { uint4 v; asm volatile("ld.weak.global.L1::no_allocate.v4.u32 {%0,%1,%2,%3}, [%4];" : "=r"(v.x), "=r"(v.y), "=r"(v.z), "=r"(v.w) : "l"(a) : "memory"); return v; }
__device__ __forceinline__ void mma_k8(float* c, uint2 a, uint32_t b) {
    asm volatile("mma.sync.aligned.m16n8k8.row.col.f32.bf16.bf16.f32 {%0,%1,%2,%3}, {%4,%5}, {%6}, {%0,%1,%2,%3};"
                 : "+f"(c[0]), "+f"(c[1]), "+f"(c[2]), "+f"(c[3]) : "r"(a.x), "r"(a.y), "r"(b));
}
__device__ __forceinline__ void mma_k16(float* d, uint2 a, uint2 a2, uint32_t b0, uint32_t b1, float c0, float c1, float c2, float c3) {
    asm volatile("mma.sync.aligned.m16n8k16.row.col.f32.bf16.bf16.f32 {%0,%1,%2,%3}, {%4,%5,%6,%7}, {%8,%9}, {%10,%11,%12,%13};"
                 : "=f"(d[0]), "=f"(d[1]), "=f"(d[2]), "=f"(d[3]) : "r"(a.x), "r"(a.y), "r"(a2.x), "r"(a2.y), "r"(b0), "r"(b1), "f"(c0), "f"(c1), "f"(c2), "f"(c3));
}
__device__ __forceinline__ uint32_t pack_bias(float lo, float hi, uint32_t bias2) {
    uint32_t p, o;
    asm("cvt.rn.bf16x2.f32 %0, %1, %2;" : "=r"(p) : "f"(hi), "f"(lo));
    asm("add.rn.bf16x2 %0, %1, %2;" : "=r"(o) : "r"(p), "r"(bias2));
    return o;
}

template <bool B> struct Flag { static constexpr bool value = B; };
struct Params {
    const uint16_t* w; const uint16_t* bias; const uint8_t* x;
    int nq, npages;
    int ncl, nh;
    int nctas;
    int tb, ta, te, slope0, slope1, c0;
    int m0;
    uint32_t ratio[8]; int rm[8];
};
struct Maps { CUtensorMap x[2], o[2], pf; };
__device__ __forceinline__ uint4 entry_w(int M, int w, int q, int extra) {
    const int r = M - ((M + 32) >> 6), o = (r * 9363) >> 16, t = r - 7 * o, odd = t & 1, n = t >> 1;
    const int u = w ^ o ^ odd;
    const int C = 8 * o + 2 * n + ((n ^ u) & 1), C2 = 8 * o + 6 + ((1 ^ u) & 1);
    const uint32_t ra = 57 * C - ((C * 7282) >> 16) + 4 * odd, rb = odd ? 57 * C2 - ((C2 * 7282) >> 16) + 4 + 2 * n : ra + 12;
    const uint32_t rm = 2048 * (2 * (M >> 6) + w) + 56;
    const bool mixed = (M & 63) == 31;
    return make_uint4(M | (mixed << 14) | (q << 17) | (extra << 18), mixed ? rm * 0x10001u + (512u << 16) : ra * 0x10001u + (2u << 16),
                      mixed ? rm * 0x10001u + (1024u | 1536u << 16) : (ra + (odd ? 4 : 10)) | (rb << 16), 0);
}
__device__ __forceinline__ uint4 entry(int M, int q, int extra, unsigned long long plan) {
    const int r = M - ((M + 32) >> 6), page = (r * 2341) >> 16;
    return entry_w(M, (M & 63) == 31 ? q : q ^ (int)((plan >> page) & 1), q, extra);
}
__device__ __forceinline__ int frontier(const Params& p, int t) {
    t = max(t, p.tb);
    const int l = t < p.ta ? LEAD0 + ((p.slope0 * (t - p.tb)) >> 16) : LEADE + max(0, (p.slope1 * (p.te - t)) >> 16);
    return (min(p.nq, t + l) * 9) >> 3;
}
__device__ __forceinline__ uint4 cl_entry(const Params& p, int m, int q, uint32_t ratio, unsigned long long plan) {
    const int nb = (m * ratio + 0x8000u) >> 16, nb1 = m ? ((m - 1) * ratio + 0x8000u) >> 16 : 0;
    uint4 e = entry(p.m0 + m + nb, q, nb - nb1, plan);
    const int c0 = frontier(p, p.m0 + m - 1 + nb1);
    e.w = c0 | (frontier(p, p.m0 + m + nb) - c0) << 16;
    return e;
}
__device__ __forceinline__ int helpers(const Params& p, unsigned long long plan, int q) {
    const int h0 = min(max(((p.ncl + p.nh) >> 1) - (p.ncl - (int)((plan >> 48) & 0xFF)), 0), p.nh);
    return q ? p.nh - h0 : h0;
}
__device__ __forceinline__ void draw(uint32_t& v, uint32_t* ctr, uint32_t inc) {
    asm volatile("{\n.reg .pred p;\nelect.sync _|p, 0xffffffff;\n@p atom.relaxed.gpu.global.add.u32 %0, [%1], %2;\n}" : "+r"(v) : "l"(ctr), "r"(inc) : "memory");
}
__device__ __forceinline__ uint4 lds128v(uint32_t a) { uint4 v; asm volatile("ld.volatile.shared.v4.b32 {%0,%1,%2,%3}, [%4];" : "=r"(v.x), "=r"(v.y), "=r"(v.z), "=r"(v.w) : "r"(a) : "memory"); return v; }
__device__ __forceinline__ void sts128(uint32_t a, uint4 e) { asm volatile("st.shared.v4.b32 [%0], {%1,%2,%3,%4};" :: "r"(a), "r"(e.x), "r"(e.y), "r"(e.z), "r"(e.w) : "memory"); }

__device__ __forceinline__ const uint8_t* probe_line(const Params& p, int page, int cell, int line, int parity) {
    return p.x + ((size_t)page << 21) + cell * 65536 + ((__popc(cell & 0xB) ^ parity) & 1) * 4096 + line * 128;
}
__device__ __forceinline__ int lag(const uint8_t* first, const uint8_t* second, uint32_t scratch, uint32_t since) {
    uint32_t t0, t1;
#pragma unroll 1
    for (int e = 0; e < 2; e++) {
        uint32_t a = 0, b = 0;
        asm volatile("{\n.reg .pred p;\nsetp.ne.s32 p, %4, 0;\n@p ld.global.cg.u32 %0, [%2];\n@p ld.global.cg.u32 %1, [%3];\n}"
                     : "+r"(a), "+r"(b) : "l"(first), "l"(second), "r"(e) : "memory");
        asm volatile("st.volatile.shared.u32 [%0], %1;" :: "r"(scratch), "r"(a) : "memory");
        asm volatile("mov.u32 %0, %%clock;" : "=r"(t0) :: "memory");
        asm volatile("st.volatile.shared.u32 [%0], %1;" :: "r"(scratch), "r"(b) : "memory");
        asm volatile("mov.u32 %0, %%clock;" : "=r"(t1) :: "memory");
        uint32_t t = t1;
        while (t - since < PWAIT) asm volatile("mov.u32 %0, %%clock;" : "=r"(t) :: "memory");
    }
    return t1 - t0;
}

template <bool HELPER>
__global__ void __launch_bounds__(NTHREADS, 1)
spgemm_kernel(const __grid_constant__ Params p, const __grid_constant__ Maps maps) {
    extern __shared__ unsigned char smem_raw[];
    const uint32_t sb = ((uint32_t)__cvta_generic_to_shared(smem_raw) + 1023u) & ~1023u;
    const int tid = threadIdx.x, warp = __shfl_sync(~0u, tid >> 5, 0), lane = tid & 31;
    const int rank = blockIdx.x % CL, cid = blockIdx.x / CL;
    const uint32_t bar_full = sb + OFF_FULL, bar_empty = sb + OFF_EMPTY, tk = sb + OFF_TK;
    const int pr = HELPER ? 2 : rank, pc = HELPER ? blockIdx.x : cid;
    const uint8_t* pl = probe_line(p, pr == 1 ? min(pc, p.npages - 1) : p.npages - 1, pr == 1 ? 30 : pc & 31,
                                   (pr == 1 ? 4 + 2 * max(pc + 1 - p.npages, 0) : pr * 15 + (pc >> 5) * 2) + (warp & 1), warp & 1);
    uint32_t tp;
    asm volatile("mov.u32 %0, %%clock;" : "=r"(tp) :: "memory");
    if (!HELPER && warp >= 14 && lane < 2) asm volatile("prefetch.global.L2 [%0];" :: "l"((const uint8_t*)((uintptr_t)pl ^ (lane << 12))) : "memory");
    uint4 wv[4];
    const int wrow = warp * 16 + (lane & 3) * 4;
    uint32_t b0, b1;
    auto prep_load = [&](int mtile) {
        b0 = __ldg(p.bias + mtile * 64 + lane); b1 = __ldg(p.bias + mtile * 64 + 32 + lane);
#pragma unroll
        for (int j = 0; j < 4; j++) wv[j] = __ldg((const uint4*)(p.w + (rank * 192 + wrow + j) * D + mtile * 64 + (lane >> 2) * 8));
    };
    if (!HELPER && warp < 12) {
        if (cid < 36) prep_load(cid >> 2);
        asm volatile("barrier.cluster.arrive.relaxed.aligned;" ::: "memory");
    }

    if (warp >= 12) {
        asm volatile("setmaxnreg.dec.sync.aligned.u32 32;");
        if (tid == NCONS) {
#pragma unroll
            for (int s = 0; s < NSLOT; s++) { mbar_init(bar_full + 8 * s, 1); mbar_init(bar_empty + 8 * s, HELPER ? 3 : 3 * CL); }
#pragma unroll
            for (int j = 0; j < 8; j++) sts32(tk + 16 * j, 0);
            mbar_init(sb + OFF_MBAR, 1); mbar_init(sb + OFF_MBAR + 8, 1);
            mbar_init(sb + OFF_GO, HELPER ? 12 : 12 + CL); mbar_init(sb + OFF_PLAN, 1); mbar_init(sb + OFF_PLAN2, 1);
            asm volatile("fence.mbarrier_init.release.cluster;" ::: "memory");
            mbar_expect_tx(sb + OFF_MBAR, 36 * 8);
            if (!HELPER && rank != 0) mbar_expect_tx(sb + OFF_PLAN, 16);
        }
        if (tid == NCONS + 32) {
            asm volatile("prefetch.tensormap [%0];" :: "l"(&maps.x[0]) : "memory");
            if (!HELPER) asm volatile("griddepcontrol.launch_dependents;");
            asm volatile("prefetch.tensormap [%0];" :: "l"(&maps.pf) : "memory");
            asm volatile("prefetch.tensormap [%0];" :: "l"(&maps.x[1]) : "memory");
#pragma unroll
            for (int j = 0; j < 2; j++) asm volatile("prefetch.tensormap [%0];" :: "l"(&maps.o[j]) : "memory");
        }
        __syncwarp();
        auto wait_plan = [&]() -> uint4 {
            unsigned long long a, b; int n = 0;
            do { asm volatile("ld.relaxed.gpu.global.v2.u64 {%0, %1}, [%2];" : "=l"(a), "=l"(b) : "l"(&g_plan) : "memory"); fail_if(++n > (1 << 22)); }
            while (__any_sync(~0u, (int)(a >> 56) + (int)(b >> 56) != 2 * p.ncl));
            b &= (1ull << 56) - 1;
            const int side = (b >> cid) & 1, n1 = __popcll(b), below = __popcll(b & ((1ull << cid) - 1));
            a = ((a ^ b) & ((1ull << 40) - 1)) | (unsigned long long)n1 << 48;
            return make_uint4((uint32_t)a, (uint32_t)(a >> 32), side | (side ? below : cid - below) << 8 | (side ? n1 : p.ncl - n1) << 16, 0);
        };
        auto measure = [&](uint32_t since) -> int {
            const int d = lag(pl, (const uint8_t*)((uintptr_t)pl ^ 4096), sb + OFF_INFO + 16 + 4 * (warp & 1), since);
            if (warp == 14 && lane == 0) sts32(sb + OFF_INFO + 24, d);
            asm volatile("bar.sync 11, 64;" ::: "memory");
            return d > (int)lds32v(sb + OFF_INFO + 24);
        };
        uint4 e0 = make_uint4(0, 0, 0, 0), e1 = e0;
        if (HELPER) {
            asm volatile("bar.sync 0;" ::: "memory");
            int side = 0;
            if (warp >= 14) side = measure(tp - PWAIT);
            if (warp == 15) {
                uint32_t old = 0;
                if (lane == 0) {
                    old = atomicAdd(&g_hreg[rank * 32], side ? 0x10000u : 1u);
                    if ((old & 0xFFFF) + (old >> 16) == p.nh - 1) g_hreg[rank * 32] = 0;
                }
                const uint4 inf = wait_plan();
                const unsigned long long plan = inf.x | ((unsigned long long)inf.y << 32);
                old = __shfl_sync(~0u, old, 0);
                int idx = side ? p.nh - 1 - (old >> 16) : old & 0xFFFF, nh = helpers(p, plan, 0), q = 0;
                if (idx >= nh) { idx -= nh; nh = p.nh - nh; q ^= 1; }
                const uint32_t ratio = p.ratio[nh];
                const int rm = p.rm[nh], H = p.nq - p.m0 - rm;
                for (int j0 = 0; __any_sync(~0u, idx + (j0 - 1) * nh < H); j0 += 32) {
                    const int k = idx + (j0 + lane) * nh, mk = (((k + 1) << 16) - 0x8000u + ratio - 1) / ratio;
                    uint4 e = entry(p.m0 + min(mk, rm) + k, q, 0, plan);
                    if (k >= H) e.x = NO_TILE;
                    sts128(sb + OFF_TAB + 16 * (j0 + lane), e);
                }
                __syncwarp();
                if (lane == 0) mbar_arrive(sb + OFF_PLAN);
            }
        } else {
            asm volatile("barrier.cluster.arrive.relaxed.aligned;" ::: "memory");
            if (warp == 12) { e0 = entry_w(cid, 0, 0, 0); e1 = entry_w(cid, 1, 1, 0); }
            if (rank < 2 && warp >= 14) {
                const int side = measure(tp);
                if (warp == 15 && lane == 0) asm volatile("red.relaxed.gpu.global.add.u64 [%0], %1;" :: "l"(rank ? &g_plan.x : &g_plan.y), "l"((1ull << 56) | (unsigned long long)side << cid) : "memory");
            }
            asm volatile("barrier.cluster.wait.aligned;" ::: "memory");
            if (warp >= 13) {
                if (warp == 15 && rank == 0) {
                    const uint4 inf = wait_plan();
                    if (lane == 0) sts128(sb + OFF_INFO, inf);
                    else if (lane < CL)
                        asm volatile("st.async.weak.shared::cluster.mbarrier::complete_tx::bytes.v4.u32 [%0], {%1, %2, %3, %4}, [%5];"
                                     :: "r"(mapa(sb + OFF_INFO, lane)), "r"(inf.x), "r"(inf.y), "r"(inf.z), "r"(inf.w), "r"(mapa(sb + OFF_PLAN, lane)) : "memory");
                }
                if (rank == 0) asm volatile("bar.sync 15, 96;" ::: "memory"); else mbar_wait(sb + OFF_PLAN, 0);
                const uint4 inf = lds128v(sb + OFF_INFO);
                const unsigned long long plan = inf.x | ((unsigned long long)inf.y << 32);
                const int nh = helpers(p, plan, inf.z & 1), rm = p.rm[nh], nc = inf.z >> 16;
                const uint32_t ratio = p.ratio[nh];
                if (warp == 15 && rank == 0) {
                    const int m = ((inf.z >> 8) & 0xFF) + min(lane, NSTAT - 1) * nc;
                    sts128(sb + OFF_TAB + 16 * m, cl_entry(p, m, inf.z & 1, ratio, plan));
                    __syncwarp();
                    if (lane == 0) { mbar_arrive(sb + OFF_PLAN); mbar_expect_tx(sb + OFF_PLAN2, 16 * (rm - NSTAT * nc)); }
                }
                const uint32_t rtab = mapa(sb + OFF_TAB, 0), rbar = mapa(sb + OFF_PLAN2, 0);
                for (int m0 = NSTAT * nc + 96 * (2 - rank); __any_sync(~0u, m0 < rm); m0 += 288) {
                    const int m = m0 + tid - (NCONS + 32);
                    const uint4 e = cl_entry(p, m, inf.z & 1, ratio, plan);
                    if (m < rm) asm volatile("st.async.weak.shared::cluster.mbarrier::complete_tx::bytes.v4.u32 [%0], {%1, %2, %3, %4}, [%5];"
                                             :: "r"(rtab + 16 * m), "r"(e.x), "r"(e.y), "r"(e.z), "r"(e.w), "r"(rbar) : "memory");
                }
            }
        }
        if (warp == 12) {
            if (!HELPER && rank != 0) {
                mbar_wait(sb + OFF_PLAN, 0);
                const uint4 inf = lds128v(sb + OFF_INFO);
                const unsigned long long plan = inf.x | ((unsigned long long)inf.y << 32);
                auto cell = [&](int c, int q) {
                    const int y = 32 * c - 2 + 4 * ((__popc(c & 0xB) ^ (int)(plan >> (c >> 5)) ^ q) & 1);
                    asm volatile("{\n.reg .pred p;\nelect.sync _|p, 0xffffffff;\n@p cp.async.bulk.prefetch.tensor.3d.L2.global.tile [%0, {%1, %2, %1}];\n}" :: "l"(&maps.pf), "r"(0), "r"(y) : "memory");
                };
                const int fe0 = frontier(p, 0), step = 2 * (inf.z >> 16);
                int u0 = p.c0 + 2 * ((inf.z >> 8) & 0xFF) + rank - 1;
                {
                    uint32_t t, due;
                    asm volatile("mov.u32 %0, %%clock;" : "=r"(due) :: "memory");
                    due += (PACE * (u0 - p.c0)) / step;
                    for (; __any_sync(~0u, u0 < fe0); u0 += step, due += PACE) {
                        do { asm volatile("mov.u32 %0, %%clock;" : "=r"(t) :: "memory"); } while (__any_sync(~0u, (int)(t - due) < 0));
                        cell(u0, inf.z & 1);
                    }
                }
                for (int j = XEARLY + rank - 1;; j += 2) {
                    uint4 v; uint32_t ahead;
                    for (int n = 0; __any_sync(~0u, (ahead = (((v = lds128v(tk + ((j & 7) << 4))).x >> 20) - (j + 1)) & 0xFFF) >= 0x800); n++) {
                        if (__any_sync(~0u, lds32v(tk + (((j - 1) & 7) << 4)) == (NO_TILE | (uint32_t)j << 20))) { v.x = NO_TILE; break; }
                        __nanosleep(100); fail_if(n > (1 << 24));
                    }
                    if (__any_sync(~0u, (v.x & NO_TILE) == NO_TILE)) break;
                    j += __reduce_max_sync(~0u, ahead);
                    for (int u = v.w & 0xFFFF; __any_sync(~0u, u < (v.w & 0xFFFF) + (v.w >> 16)); u++) cell(u, (v.x >> 17) & 1);
                }
            } else {
                const uint32_t rtk = HELPER ? tk : mapa(tk, lane < CL ? lane : 0), rfull = HELPER ? bar_full : mapa(bar_full, lane < CL ? lane : 0);
                int s = 0; uint32_t ph = 1;
                uint64_t pol;
                if (!HELPER) asm volatile("createpolicy.fractional.L2::evict_first.b64 %0, 1.0;" : "=l"(pol));
                else asm volatile("createpolicy.fractional.L2::evict_normal.b64 %0, 1.0;" : "=l"(pol));
                auto request = [&](int j, const uint4& t) {
                    const bool valid = t.x != NO_TILE;
                    const CUtensorMap* tm = &maps.x[(t.x >> 14) & 1];
                    mbar_wait(bar_empty + 8 * s, ph);
                    if (__any_sync(~0u, valid)) {
                        const uint32_t dst = sb + OFF_X + s * TILE_BYTES;
                        if (HELPER)
                            asm volatile("{\n.reg .pred p;\nelect.sync _|p, 0xffffffff;\n"
                                         "@p cp.async.bulk.tensor.4d.shared::cluster.global.mbarrier::complete_tx::bytes.L2::cache_hint [%0], [%4, {%6, %7, %6, %6}], [%5], %11;\n"
                                         "@p cp.async.bulk.tensor.4d.shared::cluster.global.mbarrier::complete_tx::bytes.L2::cache_hint [%1], [%4, {%6, %8, %6, %6}], [%5], %11;\n"
                                         "@p cp.async.bulk.tensor.4d.shared::cluster.global.mbarrier::complete_tx::bytes.L2::cache_hint [%2], [%4, {%6, %9, %6, %6}], [%5], %11;\n"
                                         "@p cp.async.bulk.tensor.4d.shared::cluster.global.mbarrier::complete_tx::bytes.L2::cache_hint [%3], [%4, {%6, %10, %6, %6}], [%5], %11;\n}\n"
                                         :: "r"(dst), "r"(dst + 9216), "r"(dst + 2 * 9216), "r"(dst + 3 * 9216), "l"(tm), "r"(bar_full + 8 * s), "r"(0),
                                            "r"(t.y & 0xFFFF), "r"(t.y >> 16), "r"(t.z & 0xFFFF), "r"(t.z >> 16), "l"(pol) : "memory");
                        else
                            asm volatile("{\n.reg .pred p;\nelect.sync _|p, 0xffffffff;\n"
                                         "@p cp.async.bulk.tensor.4d.shared::cluster.global.mbarrier::complete_tx::bytes.multicast::cluster.L2::cache_hint [%0], [%4, {%6, %7, %6, %6}], [%5], %11, %12;\n"
                                         "@p cp.async.bulk.tensor.4d.shared::cluster.global.mbarrier::complete_tx::bytes.multicast::cluster.L2::cache_hint [%1], [%4, {%6, %8, %6, %6}], [%5], %11, %12;\n"
                                         "@p cp.async.bulk.tensor.4d.shared::cluster.global.mbarrier::complete_tx::bytes.multicast::cluster.L2::cache_hint [%2], [%4, {%6, %9, %6, %6}], [%5], %11, %12;\n"
                                         "@p cp.async.bulk.tensor.4d.shared::cluster.global.mbarrier::complete_tx::bytes.multicast::cluster.L2::cache_hint [%3], [%4, {%6, %10, %6, %6}], [%5], %11, %12;\n}\n"
                                         :: "r"(dst), "r"(dst + 9216), "r"(dst + 2 * 9216), "r"(dst + 3 * 9216), "l"(tm), "r"(bar_full + 8 * s), "r"(0),
                                            "r"(t.y & 0xFFFF), "r"(t.y >> 16), "r"(t.z & 0xFFFF), "r"(t.z >> 16), "h"((uint16_t)((1u << CL) - 1)), "l"(pol) : "memory");
                    }
                    if (HELPER) {
                        if (lane == 0) { sts128(tk + ((j & 7) << 4), t); mbar_expect_tx(bar_full + 8 * s, valid ? TILE_BYTES : 0); }
                    } else if (lane < CL) {
                        asm volatile("mbarrier.arrive.expect_tx.shared::cluster.b64 _, [%0], %1;" :: "r"(rfull + 8 * s), "r"(valid ? TILE_BYTES + 16 : 16) : "memory");
                        asm volatile("st.async.weak.shared::cluster.mbarrier::complete_tx::bytes.v4.u32 [%0], {%1, %2, %3, %4}, [%5];"
                                     :: "r"(rtk + ((j & 7) << 4)), "r"(t.x | ((uint32_t)(j + 1) << 20)), "r"(t.y), "r"(t.z), "r"(t.w), "r"(rfull + 8 * s) : "memory");
                    }
                    if (++s == NSLOT) { s = 0; ph ^= 1; }
                };
                if (HELPER) {
#pragma unroll 1
                    for (int j = 0; j < XEARLY; j++) request(j, entry_w(p.ncl + cid + (j >> 1) * (p.ncl + p.nh), j & 1, j & 1, 0));
                    mbar_wait(sb + OFF_PLAN, 0);
                    mbar_wait(sb + OFF_GO, 0);
                    for (int j = XEARLY;; j++) {
                        const uint4 t = lds128v(sb + OFF_TAB + 16 * (j - XEARLY));
                        request(j, t);
                        if (__any_sync(~0u, t.x == NO_TILE)) break;
                    }
                } else {
                    static_assert(XEARLY == 2, "");
                    request(0, e0);
                    request(1, e1);
                    mbar_wait(sb + OFF_PLAN, 0);
                    const uint4 inf = lds128v(sb + OFF_INFO);
                    const unsigned long long plan = inf.x | ((unsigned long long)inf.y << 32);
                    const int side = inf.z & 1, nc = inf.z >> 16;
                    const int nh = helpers(p, plan, side), rm = p.rm[nh], rmo = p.rm[p.nh - nh];
                    const uint32_t ratio = p.ratio[nh], ratioo = p.ratio[p.nh - nh];
                    const int st = NSTAT * nc, sto = NSTAT * (p.ncl - nc);
                    uint4 t = lds128v(sb + OFF_TAB + 16 * ((inf.z >> 8) & 0xFF));
                    mbar_wait(sb + OFF_GO, 0);
                    int j = XEARLY;
#pragma unroll 1
                    for (; j < XEARLY + NSTAT - 2; j++) {
                        const uint4 tn = lds128v(sb + OFF_TAB + 16 * (((inf.z >> 8) & 0xFF) + (j + 1 - XEARLY) * nc));
                        request(j, t);
                        t = tn;
                    }
                    uint32_t drawn = 0;
                    int q = side;
                    request(j++, t);
                    draw(drawn, &g_ticket, 1u << (16 * side));
                    t = lds128v(sb + OFF_TAB + 16 * (((inf.z >> 8) & 0xFF) + (NSTAT - 1) * nc));
                    mbar_wait(sb + OFF_PLAN2, 0);
                    for (;; j++) {
                        request(j, t);
                        uint32_t v = __reduce_max_sync(~0u, drawn);
                        int m = st + ((v >> (16 * side)) & 0xFFFF), mo = sto + ((v >> (16 - 16 * side)) & 0xFFFF);
                        if (q == side ? m >= rm && mo < rmo : mo >= rmo && m < rm) {
                            q ^= 1;
                            draw(drawn, &g_ticket, 1u << (16 * q));
                            v = __reduce_max_sync(~0u, drawn);
                            m = st + ((v >> (16 * side)) & 0xFFFF); mo = sto + ((v >> (16 - 16 * side)) & 0xFFFF);
                        }
                        if (q == side ? m >= rm : mo >= rmo) break;
                        const bool own = q == side;
                        q = m + ((m * ratio) >> 16) > mo + ((mo * ratioo) >> 16) + DELTA ? side ^ 1 : side;
                        draw(drawn, &g_ticket, 1u << (16 * q));
                        if (own) t = lds128v(sb + OFF_TAB + 16 * m);
                        else t = cl_entry(p, mo, side ^ 1, ratioo, plan);
                    }
                    t.x = NO_TILE;
                    request(j + 1, t);
                    if (lane == 0 && atomicInc(&g_done, p.ncl - 1) == (uint32_t)p.ncl - 1) g_ticket = 0;
                }
            }
        } else {
            const int g = warp - 13;
            uint64_t spol;
            asm volatile("createpolicy.fractional.L2::evict_first.b64 %0, 1.0;" : "=l"(spol));
            mbar_wait(sb + OFF_GO, 0);
            if (g == 2 && lane == 0 && atomicInc(&g_passed, p.nctas - 1) == (uint32_t)p.nctas - 1) {
#pragma unroll
                for (int m = 0; m < 36; m++) g_ready[m * 32] = 0;
                g_plan = make_ulonglong2(0, 0);
            }
            __syncwarp();
            for (int i = 0;; i++) {
                asm volatile("bar.arrive %0, 160;" :: "r"(12 + g) : "memory");
                asm volatile("bar.sync %0, 160;" :: "r"(1 + g) : "memory");
                const uint4 t = lds128v(tk + ((i & 7) << 4));
                if ((t.x & NO_TILE) == NO_TILE) break;
                const CUtensorMap* tm = &maps.o[(t.x >> 14) & 1];
                const int row[4] = {(int)(t.y & 0xFFFF), (int)(t.y >> 16), (int)(t.z & 0xFFFF), (int)(t.z >> 16)};
                if (lane == 0) {
#pragma unroll
                    for (int k = 0; k < 4; k++)
                        asm volatile("cp.async.bulk.tensor.3d.global.shared::cta.bulk_group.L2::cache_hint [%0, {%2, %3, %4}], [%1], %5;"
                                     :: "l"(tm), "r"(sb + OFF_STG + (g + 3 * (i & 1)) * STG_BYTES + k * 1024), "r"((g * 3 + rank) * 64), "r"(row[k]), "r"(0), "l"(spol) : "memory");
                    asm volatile("cp.async.bulk.commit_group;" ::: "memory");
                    asm volatile("cp.async.bulk.wait_group.read 1;" ::: "memory");
                }
                __syncwarp();
            }
            if (lane == 0) asm volatile("cp.async.bulk.wait_group.read 0;" ::: "memory");
        }
        __syncwarp();
        if (!HELPER) asm volatile("barrier.cluster.arrive.relaxed.aligned;\nbarrier.cluster.wait.aligned;" ::: "memory");
    } else {
        asm volatile("setmaxnreg.inc.sync.aligned.u32 160;");
        const int wg = warp >> 2, wtid = tid & 127;
        if (HELPER) asm volatile("bar.sync 0;" ::: "memory");
        else {
            int prb = cid;
            if (prb >= 36) asm volatile("barrier.cluster.wait.aligned;" ::: "memory");
#pragma unroll 1
            for (int round = 0; prb < 36; prb += p.ncl, round++) {
                const uint32_t wsm = sb + OFF_WST, msk = sb + OFF_MSK + (round & 1) * 288, mbar = sb + OFF_MBAR + (round & 1) * 8;
                if (round) {
                    asm volatile("bar.sync 3, 384;" ::: "memory");
                    if (tid == 0) mbar_expect_tx(mbar, 36 * 8);
                    prep_load(prb >> 2);
                }
                const int nt = ties(wv[0].x, wv[1].x, wv[2].x, wv[3].x) + ties(wv[0].y, wv[1].y, wv[2].y, wv[3].y) +
                               ties(wv[0].z, wv[1].z, wv[2].z, wv[3].z) + ties(wv[0].w, wv[1].w, wv[2].w, wv[3].w);
                const uint32_t mk = __ballot_sync(~0u, nt > 0), md = __ballot_sync(~0u, nt > 1);
                if (round == 0) asm volatile("barrier.cluster.wait.aligned;" ::: "memory");
                if (lane < CL)
                    asm volatile("st.async.weak.shared::cluster.mbarrier::complete_tx::bytes.v2.u32 [%0], {%1, %2}, [%3];"
                                 :: "r"(mapa(msk + (rank * 12 + warp) * 8, lane)), "r"(mk), "r"(md), "r"(mapa(mbar, lane)) : "memory");
#pragma unroll
                for (int j = 0; j < 4; j++) {
                    const int row = wrow + j;
                    const uint32_t ad = wsm + row * 128 + (((lane >> 2) ^ ((row & 1) | ((row >> 1) & 6))) << 4);
                    asm volatile("st.shared.v4.b32 [%0], {%1,%2,%3,%4};" :: "r"(ad), "r"(wv[j].x), "r"(wv[j].y), "r"(wv[j].z), "r"(wv[j].w) : "memory");
                }
                if (warp == 0) {
                    mbar_wait(mbar, (round >> 1) & 1);
                    uint4 ms = make_uint4(0, 0, 0, 0);
                    if (lane < KSTEPS) ms = lds128v(msk + 16 * lane);
                    const uint32_t te = (ms.x & 0x0F0F0F0Fu) | ((ms.z & 0x0F0F0F0Fu) << 4), to = ((ms.x >> 4) & 0x0F0F0F0Fu) | (ms.z & 0xF0F0F0F0u);
                    const uint32_t de = (ms.y & 0x0F0F0F0Fu) | ((ms.w & 0x0F0F0F0Fu) << 4), dq = ((ms.y >> 4) & 0x0F0F0F0Fu) | (ms.w & 0xF0F0F0F0u);
                    auto count = [](uint32_t v) { v -= (v >> 1) & 0x55555555u; v = (v & 0x33333333u) + ((v >> 2) & 0x33333333u); return (v + (v >> 4)) & 0x0F0F0F0Fu; };
                    const uint32_t c0 = __reduce_add_sync(~0u, count(te)), c1 = __reduce_add_sync(~0u, count(to));
                    auto byte = [](uint32_t a, uint32_t b, uint32_t u) { return __byte_perm(a, b, (u >> 1) + 4 * (u & 1)) & 0xFFu; };
                    const uint32_t ku = byte(c0, c1, lane & 7) * 8 + (lane & 7), k2 = 2 * (lane >> 3);
                    const uint32_t ranks = __reduce_add_sync(~0u, ((byte(c0, c1, k2) * 8 + k2 < ku) + (byte(c0, c1, k2 + 1) * 8 + k2 + 1 < ku)) << (4 * (lane & 7)));
                    const uint32_t order = __reduce_add_sync(~0u, lane < 8 ? lane << (4 * ((ranks >> (4 * lane)) & 7)) : 0);
                    int cnt[4]; uint32_t mq = 0;
#pragma unroll
                    for (int z = 0; z < 4; z++) {
                        const uint32_t ua = (order >> (4 * z)) & 7, ub = (order >> (28 - 4 * z)) & 7;
                        const uint32_t ta = byte(te, to, ua), tb = byte(te, to, ub), v = ta | tb | ((ta & tb) | byte(de, dq, ua) | byte(de, dq, ub)) << 8;
                        cnt[z] = __popc(v);
                        if (z == (prb & 3)) mq = v;
                    }
                    const uint32_t l01 = __reduce_add_sync(~0u, cnt[0] | cnt[1] << 16), l23 = __reduce_add_sync(~0u, cnt[2] | cnt[3] << 16);
                    const int ulo = (order >> (4 * (prb & 3))) & 7, uhi = (order >> (28 - 4 * (prb & 3))) & 7;
                    const int full = max(max(max((int)(l01 & 0xFFFF) - cnt[0], (int)(l01 >> 16) - cnt[1]), max((int)(l23 & 0xFFFF) - cnt[2], (int)(l23 >> 16) - cnt[3])), 16);
                    const int twice = __reduce_min_sync(~0u, lane < KSTEPS ? full << 12 | (65 - cnt[0] - cnt[1] - cnt[2] - cnt[3]) << 5 | lane : full << 12 | 31) & 31;
                    sts32(sb + OFF_SEL + 4 * lane, lane == 31 ? ulo | (uhi << 4) | (twice << 8) : lane == twice ? 0 : mq);
                }
                asm volatile("bar.sync 1, 384;" ::: "memory");
                const uint32_t units = lds32v(sb + OFF_SEL + 4 * 31), mq = lds32v(sb + OFF_SEL + 4 * min(lane, 30));
                uint32_t wm[4];
                load_units(wsm, warp, units & 7, (units >> 4) & 7, lane, wm);
                emit_half(wm, mq, prb, rank * 6 + (warp >> 1), warp & 1, lane, units, b0, b1);
                asm volatile("bar.sync 2, 384;" ::: "memory");
                if (tid == 0) asm volatile("red.release.gpu.global.add.u32 [%0], 1;" :: "l"(&g_ready[prb * 32]) : "memory");
            }
            if (warp == 0 && lane < CL) mbar_arrive_cluster(mapa(sb + OFF_GO, lane));
        }
        const int mt = wg * 3 + rank, rb = mt * 4 + (warp & 3);
        {
            uint32_t v; int n = 0;
            do { asm volatile("ld.acquire.gpu.global.u32 %0, [%1];" : "=r"(v) : "l"(&g_ready[rb * 32]) : "memory"); fail_if(++n > (1 << 22)); } while (__any_sync(~0u, v < CL));
        }
        if (wg > 0) asm volatile("bar.sync %0, 256;" :: "r"(7 + wg) : "memory");
        uint32_t a[KSTEPS + 1][4], meta[9];
        uint2 rv[3]; uint32_t ro[3], sel[3];
        uint32_t info, bias_lo, bias_hi;
        {
            const uint4* ap = g_aux + rb * 6 * 32 + lane;
            const uint4 v3 = ldw(ap + 96), v2 = ldw(ap + 64), v4 = ldw(ap + 128), v5 = ldw(ap + 160), v0 = ldw(ap), v1 = ldw(ap + 32);
            meta[0] = v0.x; meta[1] = v0.y; meta[2] = v0.z; meta[3] = v0.w; meta[4] = v1.x; meta[5] = v1.y; meta[6] = v1.z; meta[7] = v1.w;
            meta[8] = v2.x; info = v2.y; bias_lo = v2.z; bias_hi = v2.w;
            ro[0] = v3.x; ro[1] = v3.y; ro[2] = v3.z;
            rv[0] = make_uint2(v4.x, v4.y); rv[1] = make_uint2(v4.z, v4.w); rv[2] = make_uint2(v5.x, v5.y);
        }
#pragma unroll
        for (int k = 0; k < KSTEPS + 1; k++) { uint4 v = ldw(&g_afrag[(mt * (KSTEPS + 1) + k) * 128 + wtid]); a[k][0] = v.x; a[k][1] = v.y; a[k][2] = v.z; a[k][3] = v.w; }
        if (wg < 2) asm volatile("bar.arrive %0, 256;" :: "r"(8 + wg) : "memory");
        if (lane == 0) mbar_arrive(sb + OFF_GO);
        auto selector = [](uint32_t o) { return 0x5410u + ((o >> 15) & 1) * 0x22u + (o >> 31) * 0x2200u; };
#pragma unroll
        for (int j = 0; j < 3; j++) { sel[j] = selector(ro[j]); ro[j] &= 0x7FFF7FFFu; }
        mbar_wait(bar_full, 0);
        info = __shfl_sync(~0u, info, 0);
        const int ngrp = info & 0xFF, ulo = (info >> 8) & 7, uhi = (info >> 12) & 7;
        const uint32_t stg = sb + OFF_STG + wg * STG_BYTES + ((lane >> 4) * 8 + (lane & 7)) * 128 + (((((lane >> 3) & 1) ? uhi : ulo) ^ (lane & 7)) << 4);
        const uint32_t twice = (((info >> 17) & 15) * 1024 + ((info >> 16) & 1) * 64) >> 4;
        const uint32_t rempty = HELPER ? bar_empty : mapa(bar_empty, 0);
        float acc[NACC];
        uint32_t bq[NB][6];
        auto gather = [&](uint32_t xb) {
#pragma unroll
            for (int j = 0; j < 4; j++) {
                const uint32_t o = xb + ((j & 1) ? ro[j >> 1] >> 16 : ro[j >> 1] & 0xFFFF);
#pragma unroll
                for (int n = 0; n < NB; n++) {
                    if (j < 3) { bq[n][j] = lds32(o + n * 9216); continue; }
                    bq[n][j] = 0;
                    asm volatile("{\n.reg .pred p;\nsetp.lt.s32 p, %2, %3;\n@p ld.shared.b32 %0, [%1];\n}" : "+r"(bq[n][j]) : "r"(o + n * 9216), "r"(j), "r"(ngrp) : "memory");
                }
            }
        };
        auto select = [&]() {
#pragma unroll
            for (int n = 0; n < NB; n++)
#pragma unroll
                for (int j = 0; j < 2; j++) bq[n][2 * j] = __byte_perm(bq[n][2 * j], bq[n][2 * j + 1], sel[j]);
        };
        auto further = [&](uint32_t xb, int bar) {
#pragma unroll 1
            for (int y = 4; y < min(ngrp, 5); y++) {
#pragma unroll
                for (int n = 0; n < NB; n++) { bq[n][4] = lds32(xb + (ro[2] & 0xFFFF) + n * 9216); bq[n][5] = lds32(xb + (ro[2] >> 16) + n * 9216); }
#pragma unroll
                for (int n = 0; n < NB; n++) mma_k8(acc + 4 * n, rv[2], __byte_perm(bq[n][4], bq[n][5], sel[2]));
                if (bar >= 0) asm volatile("bar.arrive %0, 256;" :: "r"(bar) : "memory");
#pragma unroll 1
                for (int z = 3; 2 * z < ngrp; z++) {
                    const uint2 v = __ldca(&g_rval[(rb * 36 + z) * 32 + lane]); const uint32_t off = __ldca(&g_roff[(rb * 36 + z) * 32 + lane]);
                    uint32_t bx[NB];
#pragma unroll
                    for (int n = 0; n < NB; n++) bx[n] = __byte_perm(lds32(xb + (off & 0x7FFF) + n * 9216), lds32(xb + ((off >> 16) & 0x7FFF) + n * 9216), selector(off));
#pragma unroll
                    for (int n = 0; n < NB; n++) mma_k8(acc + 4 * n, v, bx[n]);
                }
            }
        };
        bool more = true;
#pragma unroll
        for (int n = 0; n < NB; n++) bq[n][4] = bq[n][5] = 0;
        gather(sb + OFF_X);
        select();
#pragma unroll
        for (int n = 0; n < NB; n++) mma_k16(acc + 4 * n, rv[0], rv[1], bq[n][0], bq[n][2], 0.f, 0.f, 0.f, 0.f);
        further(sb + OFF_X, -1);
        const int bar_a = 8 + wg, bar_an = 8 + (wg + 2) % 3, bar_tn = 4 + (wg + 2) % 3;
        if (wg == 1) asm volatile("bar.arrive 4, 256;" ::: "memory");
        if (wg == 2) { asm volatile("bar.sync 10, 256;" ::: "memory"); asm volatile("bar.arrive 5, 256;" ::: "memory"); }
        auto run = [&](auto tw) {
        constexpr bool TW = decltype(tw)::value;
        int s = 0; uint32_t ph = 0;
        bool ready = false;
        for (int i = 0; more; i++) {
            const uint32_t xb = sb + OFF_X + s * TILE_BYTES;
            const int s1 = s + 1 == NSLOT ? 0 : s + 1;
            const uint32_t ph1 = s1 == 0 ? ph ^ 1 : ph;
            asm volatile("bar.sync %0, 256;" :: "r"(4 + wg) : "memory");
            const uint64_t desc = ((uint64_t)1 << 62) | ((uint64_t)(9216 >> 4) << 32) | ((uint64_t)1 << 16) | (uint64_t)(xb >> 4);
            asm volatile("wgmma.fence.sync.aligned;" ::: "memory");
#pragma unroll
            for (int k = 0; k < KSTEPS; k++) {
                const uint64_t d = desc + (uint64_t)(((k >> 1) * 1024 + (k & 1) * 64) >> 4);
                if (k & 1) wgmma_sp<1>(acc, a[k], d, meta[k >> 1]);
                else       wgmma_sp<0>(acc, a[k], d, meta[k >> 1]);
            }
            if (TW) wgmma_sp<0>(acc, a[KSTEPS], desc + twice, 0x44444444u);
            asm volatile("wgmma.commit_group.sync.aligned;" ::: "memory");
            asm volatile("bar.arrive %0, 256;" :: "r"(bar_an) : "memory");
            if (!ready) mbar_wait(bar_full + 8 * s1, ph1);
            const uint32_t tn = lds32v(tk + (((i + 1) & 7) << 4));
            gather(sb + OFF_X + s1 * TILE_BYTES);
            asm volatile("bar.sync %0, 160;" :: "r"(12 + wg) : "memory");
            asm volatile("wgmma.wait_group.sync.aligned 0;" ::: "memory");
            const uint32_t sg = stg + (i & 1) * (3 * STG_BYTES);
            if (wtid == 0) { if (HELPER) mbar_arrive(bar_empty + 8 * s); else mbar_arrive_cluster(rempty + 8 * s); }
#pragma unroll
            for (int n = 0; n < NB; n += 2) {
                const uint32_t p0 = pack_bias(acc[4 * n], acc[4 * n + 1], bias_lo), p1 = pack_bias(acc[4 * n + 2], acc[4 * n + 3], bias_hi);
                const uint32_t p2 = pack_bias(acc[4 * n + 4], acc[4 * n + 5], bias_lo), p3 = pack_bias(acc[4 * n + 6], acc[4 * n + 7], bias_hi);
                if (n == 0) asm volatile("stmatrix.sync.aligned.m8n8.x4.trans.shared.b16 [%0], {%1,%2,%3,%4};" :: "r"(sg + n * 1024), "r"(p0), "r"(p1), "r"(p2), "r"(p3) : "memory");
                else asm volatile("{\n.reg .pred p;\nAGAIN:\nstmatrix.sync.aligned.m8n8.x4.trans.shared.b16 [%0], {%1,%2,%3,%4};\nsetp.eq.u32 p, %5, 0xFFFFFFFE;\n@p bra.uni AGAIN;\n}"
                                  :: "r"(sg + n * 1024), "r"(p0), "r"(p1), "r"(p2), "r"(p3), "r"(info) : "memory");
            }
            more = __any_sync(~0u, (tn & NO_TILE) != NO_TILE);
            select();
            if (wg != 2 || more) {
                asm volatile("{\n.reg .pred p;\nTURN:\nbar.sync %0, 256;\nsetp.eq.u32 p, %1, 0xFFFFFFFF;\n@p bra.uni TURN;\n}" :: "r"(bar_a), "r"(info) : "memory");
#pragma unroll
                for (int n = 0; n < NB; n++) {
                    mma_k16(acc + 4 * n, rv[0], rv[1], bq[n][0], bq[n][2], 0.f, 0.f, 0.f, 0.f);
                    if (n == 0) asm volatile("{\n.reg .pred p;\nsetp.le.s32 p, %1, 4;\n@p bar.arrive %0, 256;\n}" :: "r"(bar_tn), "r"(ngrp) : "memory");
                }
                further(sb + OFF_X + s1 * TILE_BYTES, bar_tn);
            }
            asm volatile("fence.proxy.async.shared::cta;" ::: "memory");
            asm volatile("bar.arrive %0, 160;" :: "r"(1 + wg) : "memory");
            s = s1; ph = ph1;
            ready = __all_sync(~0u, mbar_test(bar_full + 8 * (s + 1 == NSLOT ? 0 : s + 1), s + 1 == NSLOT ? ph ^ 1 : ph));
        }
        };
        if (((info >> 16) & 31) < KSTEPS) run(Flag<true>()); else run(Flag<false>());
        if (wg == 0) asm volatile("bar.sync 4, 256;" ::: "memory");
        asm volatile("bar.sync %0, 160;" :: "r"(12 + wg) : "memory");
        asm volatile("bar.arrive %0, 160;" :: "r"(1 + wg) : "memory");
        if (!HELPER) asm volatile("barrier.cluster.arrive.relaxed.aligned;\nbarrier.cluster.wait.aligned;" ::: "memory");
    }
}

typedef CUresult (*EncodeFn)(CUtensorMap*, CUtensorMapDataType, cuuint32_t, void*, const cuuint64_t*, const cuuint64_t*, const cuuint32_t*, const cuuint32_t*,
                             CUtensorMapInterleave, CUtensorMapSwizzle, CUtensorMapL2promotion, CUtensorMapFloatOOBfill);

__global__ void plain_kernel(const __nv_bfloat16* x, const __nv_bfloat16* w, const __nv_bfloat16* b, __nv_bfloat16* out, int ntok) {
    const int t0 = blockIdx.x * 8;
    for (int f = threadIdx.x; f < D; f += blockDim.x) {
        float acc[8] = {};
        for (int g = 0; g < D / 4; g++) {
            float v[4], m[4];
            for (int i = 0; i < 4; i++) { v[i] = __bfloat162float(w[(4 * g + i) * D + f]); m[i] = fabsf(v[i]); }
            const float thr = fmaxf(fminf(fmaxf(m[0], m[1]), fmaxf(m[2], m[3])), fmaxf(fminf(m[0], m[1]), fminf(m[2], m[3])));
            for (int i = 0; i < 4; i++)
                for (int t = 0; t < 8; t++)
                    if (m[i] >= thr && t0 + t < ntok) acc[t] += v[i] * __bfloat162float(x[(size_t)(t0 + t) * D + 4 * g + i]);
        }
        for (int t = 0; t < 8; t++)
            if (t0 + t < ntok) out[(size_t)(t0 + t) * D + f] = __hadd(__float2bfloat16(acc[t]), b[f]);
    }
}

extern "C" void kernel_launch(void* const* d_in, const int* in_sizes, int n_in, void* d_out, int out_size) {
    static EncodeFn enc = nullptr;
    static int ncl = 0, nhelp = 0;
    const int ntok = in_sizes[0] / D;
    cudaLaunchConfig_t cfg = {};
    cudaLaunchAttribute at[1];
    at[0].id = cudaLaunchAttributeClusterDimension; at[0].val.clusterDim.x = CL; at[0].val.clusterDim.y = 1; at[0].val.clusterDim.z = 1;
    cfg.blockDim = dim3(NTHREADS); cfg.dynamicSmemBytes = SMEM_BYTES; cfg.attrs = at; cfg.numAttrs = 1; cfg.stream = cudaStreamPerThread;
    if (!enc) {
        cudaDriverEntryPointQueryResult qr; void* fn = nullptr;
        cudaGetDriverEntryPoint("cuTensorMapEncodeTiled", &fn, cudaEnableDefault, &qr);
        enc = (EncodeFn)fn;
        cudaFuncSetAttribute(spgemm_kernel<false>, cudaFuncAttributeMaxDynamicSharedMemorySize, SMEM_BYTES);
        cudaFuncSetAttribute(spgemm_kernel<true>, cudaFuncAttributeMaxDynamicSharedMemorySize, SMEM_BYTES);
        int dev = 0, nsm = 0;
        cudaGetDevice(&dev);
        cudaDeviceGetAttribute(&nsm, cudaDevAttrMultiProcessorCount, dev);
        cfg.gridDim = dim3(CL * (nsm / CL));
        cudaOccupancyMaxActiveClusters(&ncl, spgemm_kernel<false>, &cfg);
        if (ncl < 1) ncl = 1;
        nhelp = nsm > CL * ncl ? (nsm - CL * ncl) / CL : 0;
        if (nhelp > 7) nhelp = 7;
    }
    if (ntok % 4096 || ntok < 16384 || ntok > 65536 || ncl < 2 || ncl > 56 || ncl < CL * nhelp || 8 * (ncl + nhelp) > ntok / 64) {
        plain_kernel<<<(ntok + 7) / 8, 192, 0, cudaStreamPerThread>>>((const __nv_bfloat16*)d_in[0], (const __nv_bfloat16*)d_in[1], (const __nv_bfloat16*)d_in[2], (__nv_bfloat16*)d_out, ntok);
        return;
    }
    Maps maps;
    for (int v = 0; v < 2; v++) {
        const cuuint32_t rows = v == 0 ? 2 : 1;
        const cuuint64_t pitch = (v == 0 ? 14 : 57) * D * 2;
        {
            cuuint64_t dims[4] = {64, (cuuint64_t)ntok, 8 / rows, 9};
            cuuint64_t strides[3] = {D * 2, pitch, 128};
            cuuint32_t box[4] = {64, rows, 8 / rows, 9}, es[4] = {1, 1, 1, 1};
            enc(&maps.x[v], CU_TENSOR_MAP_DATA_TYPE_BFLOAT16, 4, d_in[0], dims, strides, box, es, CU_TENSOR_MAP_INTERLEAVE_NONE,
                CU_TENSOR_MAP_SWIZZLE_128B, CU_TENSOR_MAP_L2_PROMOTION_L2_128B, CU_TENSOR_MAP_FLOAT_OOB_FILL_NONE);
        }
        {
            cuuint64_t dims[3] = {D, (cuuint64_t)ntok, 8 / rows};
            cuuint64_t strides[2] = {D * 2, pitch};
            cuuint32_t box[3] = {64, rows, 8 / rows}, es[3] = {1, 1, 1};
            enc(&maps.o[v], CU_TENSOR_MAP_DATA_TYPE_BFLOAT16, 3, d_out, dims, strides, box, es, CU_TENSOR_MAP_INTERLEAVE_NONE,
                CU_TENSOR_MAP_SWIZZLE_128B, CU_TENSOR_MAP_L2_PROMOTION_NONE, CU_TENSOR_MAP_FLOAT_OOB_FILL_NONE);
        }
    }
    {
        cuuint64_t dims[3] = {256, (cuuint64_t)ntok * D * 2 / 2048, 4};
        cuuint64_t strides[2] = {2048, 16384};
        cuuint32_t box[3] = {256, 4, 4}, es[3] = {1, 1, 1};
        enc(&maps.pf, CU_TENSOR_MAP_DATA_TYPE_FLOAT64, 3, d_in[0], dims, strides, box, es, CU_TENSOR_MAP_INTERLEAVE_NONE,
            CU_TENSOR_MAP_SWIZZLE_NONE, CU_TENSOR_MAP_L2_PROMOTION_NONE, CU_TENSOR_MAP_FLOAT_OOB_FILL_NONE);
    }
    Params p;
    p.w = (const uint16_t*)d_in[1]; p.bias = (const uint16_t*)d_in[2]; p.x = (const uint8_t*)d_in[0];
    p.nq = ntok / 64; p.npages = (int)(((size_t)ntok * D * 2) >> 21);
    const int nc = ncl, nh = nhelp;
    p.ncl = nc; p.nh = nh; p.nctas = CL * (nc + nh);
    p.m0 = (nc + nh) * XEARLY / 2;
    for (int h = 0; h < 8; h++) {
        const uint32_t R = p.nq - p.m0, H = h * (HT * p.nq / 1024 * 44 / (nc + nh));
        p.ratio[h] = h <= nh ? (H << 16) / (R - H) : 0;
        p.rm[h] = p.ratio[h] ? (((R - 1) << 16) + 0x7FFFu) / (0x10000u + p.ratio[h]) + 1 : R;
    }
    p.c0 = (p.m0 * 9) >> 3;
    p.tb = p.m0 + (NSLOT - XEARLY) * (nc + nh) / 2;
    p.ta = p.tb + 1 + (int)((p.nq - p.tb) * TAFRAC); p.te = (int)(p.nq * TEFRAC) + 2;
    p.slope0 = ((LEAD1 - LEAD0) << 16) / (p.ta - p.tb); p.slope1 = ((LEAD1 - LEADE) << 16) / (p.te - p.ta);
    cfg.gridDim = dim3(CL * nc);
    cudaLaunchKernelEx(&cfg, spgemm_kernel<false>, p, maps);
    if (nh) {
        at[0].id = cudaLaunchAttributeProgrammaticStreamSerialization; at[0].val.programmaticStreamSerializationAllowed = 1;
        cfg.gridDim = dim3(CL * nh);
        cudaLaunchKernelEx(&cfg, spgemm_kernel<true>, p, maps);
    }
}
```

```cpp
#include <cuda_runtime.h>
#include <cuda_bf16.h>
#include <cuda.h>
#include <stdint.h>

constexpr int D = 576;
constexpr int NT = 32;
constexpr int NSLOT = 5;
constexpr int XEARLY = 2;
constexpr int NSTAT = 4;
constexpr int DELTA = 36;
constexpr int HT = 45;
constexpr int LEAD0 = 140, LEAD1 = 295, LEADE = 27, PACE = 1200;
constexpr double TAFRAC = 0.261, TEFRAC = 1.0;
constexpr int PWAIT = 1900;
constexpr int KSTEPS = 18;
constexpr int CL = 3;
constexpr int TILE_BYTES = NT * D * 2;
constexpr int STG_BYTES = NT * 128;
constexpr int NACC = NT / 2;
constexpr int NB = NT / 8;
constexpr int NCONS = 384;
constexpr int NTHREADS = 512;
constexpr int NTAB = 1024;
constexpr uint32_t NO_TILE = 0xFFFFFu;

constexpr int OFF_X = 0;
constexpr int OFF_WST = OFF_X + (NSLOT - 1) * TILE_BYTES;
constexpr int OFF_STG = OFF_X + NSLOT * TILE_BYTES;
constexpr int OFF_TAB = OFF_STG + 6 * STG_BYTES;
constexpr int OFF_TK = OFF_TAB + 16 * NTAB;
constexpr int OFF_MSK = OFF_TK + 128;
constexpr int OFF_SEL = OFF_MSK + 2 * 36 * 8;
constexpr int OFF_INFO = OFF_SEL + 128;
constexpr int OFF_FULL = OFF_INFO + 32;
constexpr int OFF_EMPTY = OFF_FULL + 8 * NSLOT;
constexpr int OFF_MBAR = OFF_EMPTY + 8 * NSLOT;
constexpr int OFF_GO = OFF_MBAR + 16;
constexpr int OFF_PLAN = OFF_GO + 8;
constexpr int OFF_PLAN2 = OFF_PLAN + 8;
constexpr int SMEM_BYTES = OFF_PLAN2 + 8 + 1024;
static_assert(SMEM_BYTES <= 232448 && TILE_BYTES >= 192 * 128 && XEARLY % 2 == 0 && XEARLY < NSLOT && NSLOT < 8 && NB == 4 && OFF_INFO % 16 == 0, "layout");

__device__ __align__(128) uint4    g_afrag[9 * (KSTEPS + 2) * 128];
__device__ __align__(128) uint4    g_aux[36 * 6 * 32];
__device__ __align__(128) uint2    g_rval[36 * 36 * 32];
__device__ __align__(128) uint32_t g_roff[36 * 36 * 32];
__device__ __align__(128) uint32_t g_ready[36 * 32];
__device__ __align__(128) uint32_t g_passed;
__device__ __align__(128) uint32_t g_ticket;
__device__ __align__(128) uint32_t g_hreg[3 * 32];
__device__ __align__(128) uint32_t g_done;
__device__ __align__(128) ulonglong2 g_plan;

__device__ __forceinline__ uint32_t max2(uint32_t a, uint32_t b) { uint32_t d; asm("max.u16x2 %0, %1, %2;" : "=r"(d) : "r"(a), "r"(b)); return d; }
__device__ __forceinline__ uint32_t min2(uint32_t a, uint32_t b) { uint32_t d; asm("min.u16x2 %0, %1, %2;" : "=r"(d) : "r"(a), "r"(b)); return d; }
__device__ __forceinline__ uint32_t sign2(uint32_t a) { uint32_t d; asm("prmt.b32 %0, %1, %1, 0xBB99;" : "=r"(d) : "r"(a)); return d; }
__device__ __forceinline__ void load_units(uint32_t wsm, int g4, int ulo, int uhi, int lane, uint32_t (&m)[4]) {
    const int row = g4 * 16 + ((lane & 7) >> 1) * 4 + ((lane >> 3) & 1) * 2 + (lane & 1);
    const uint32_t ad = wsm + row * 128 + (((lane < 16 ? ulo : uhi) ^ ((row & 1) | ((row >> 1) & 6))) << 4);
    asm volatile("ldmatrix.sync.aligned.m8n8.x4.trans.shared.b16 {%0,%1,%2,%3}, [%4];" : "=r"(m[0]), "=r"(m[1]), "=r"(m[2]), "=r"(m[3]) : "r"(ad) : "memory");
}
__device__ __forceinline__ void zip4(uint32_t a01, uint32_t a23, uint32_t b01, uint32_t b23, uint32_t (&x)[4]) {
    x[0] = __byte_perm(a01, b01, 0x5410); x[1] = __byte_perm(a01, b01, 0x7632); x[2] = __byte_perm(a23, b23, 0x5410); x[3] = __byte_perm(a23, b23, 0x7632);
}
__device__ __forceinline__ void middle2(const uint32_t (&x)[4], uint32_t (&m)[4], uint32_t& u, uint32_t& v) {
#pragma unroll
    for (int i = 0; i < 4; i++) m[i] = x[i] & 0x7FFF7FFFu;
    u = min2(max2(m[0], m[1]), max2(m[2], m[3])); v = max2(min2(m[0], m[1]), min2(m[2], m[3]));
}
__device__ __forceinline__ int ties(uint32_t x0, uint32_t x1, uint32_t x2, uint32_t x3) {
    const uint32_t x[4] = {x0, x1, x2, x3};
    uint32_t m[4], u, v;
    middle2(x, m, u, v);
    const uint32_t t = u ^ v, f = u ^ min2(min2(m[0], m[1]), min2(m[2], m[3]));
    const bool t0 = (t & 0xFFFFu) == 0 && (v & 0xFFFFu) != 0, t1 = t < 0x10000u && v >= 0x10000u;
    return t0 + t1 + 2 * ((t0 && (f & 0xFFFFu) == 0) || (t1 && f < 0x10000u));
}
__device__ __forceinline__ void split(const uint32_t (&x)[4], bool dbl, bool P, uint32_t& alo, uint32_t& ahi, uint32_t& nib, uint32_t& va, uint32_t& vb) {
    uint32_t m[4], u, v;
    middle2(x, m, u, v);
    const uint32_t c = 0x80008000u - max2(max2(u, v), 0x00010001u);
    uint32_t k0 = sign2(m[0] + c), k1 = sign2(m[1] + c), k2 = sign2(m[2] + c), k3 = sign2(m[3] + c);
    const uint32_t three = (k0 & k1 & (k2 | k3)) | (k2 & k3 & (k0 | k1)), four = k0 & k1 & k2 & k3;
    const bool a2 = !dbl && P;
    const uint32_t pa = a2 ? k2 : k0, pb = dbl ? k2 : P ? k3 : k1;
    const uint32_t ra = three & pa, rb = three & pb & (four | ~pa);
    va = (a2 ? x[2] : x[0]) & ra; vb = (dbl ? x[2] : P ? x[3] : x[1]) & rb;
    if (a2) k2 &= ~ra; else k0 &= ~ra;
    if (dbl) k2 &= ~rb; else if (P) k3 &= ~rb; else k1 &= ~rb;
    const uint32_t s1 = k1 & k0, s2 = k2 & (k0 | k1);
    const uint32_t t = (k1 & x[1]) | (~k1 & k2 & x[2]);
    const uint32_t x0 = (k0 & x[0]) | (~k0 & t), x1 = (s1 & x[1]) | (s2 & x[2]) | (k3 & x[3]);
    nib = (~k0 & k1 & 0x00010001u) | (~k0 & ~k1 & 0x00020002u) | (~s2 & 0x00040004u) | (~s1 & 0x00080008u);
    alo = __byte_perm(x0, x1, 0x5410); ahi = __byte_perm(x0, x1, 0x7632);
}
__device__ __forceinline__ uint32_t resid_off(int g, int P, int r) {
    int k0 = 4 * g + 2 * P;
    int chunk = k0 >> 6, byte = (k0 & 63) * 2;
    return chunk * 1024 + r * 128 + (((byte >> 4) ^ r) << 4) + (byte & 15);
}
__device__ __forceinline__ void emit_half(const uint32_t (&wm)[4], uint32_t md, int rb, int ks, int e, int lane, uint32_t units, uint32_t b0, uint32_t b1) {
    uint32_t* const aux = (uint32_t*)(g_aux + rb * 6 * 32);
    auto put_slot = [&](int j, int ln, uint32_t v, uint32_t off) {
        uint16_t* o = j < 6 ? (uint16_t*)aux + (3 * 32 + ln) * 8 + j : (uint16_t*)g_roff + ((rb * 36 + (j >> 1)) * 32 + ln) * 2 + (j & 1);
        uint16_t* w = j < 6 ? (uint16_t*)aux + ((4 + (j >> 2)) * 32 + ln) * 8 + (j & 2) * 2 + (j & 1) : (uint16_t*)g_rval + ((rb * 36 + (j >> 1)) * 32 + ln) * 4 + (j & 1);
        o[0] = (uint16_t)off; w[0] = (uint16_t)v; w[2] = (uint16_t)(v >> 16);
    };
    const int r = lane >> 2, q = lane & 3, g = 4 * e + q, twice = (units >> 8) & 31, twice2 = units >> 13;
    const uint32_t gm = __shfl_sync(~0u, md, ks);
    const uint32_t c2 = __popc(md & 0x5555u) | (__popc(md & 0xAAAAu) << 16);
    const uint32_t tot = __reduce_add_sync(~0u, c2), pre = __reduce_add_sync(~0u, lane < ks ? c2 : 0u);
    const int ne = tot & 0xFFFF, no = tot >> 16;
    const int rk = ((q & 1) ? pre >> 16 : pre & 0xFFFF) + __popc(gm & ((q & 1) ? 0xAAAAu : 0x5555u) & (((1u << g) - 1) * 0x101u));
    const bool dbl = (gm >> (8 + g)) & 1;
    uint32_t a0, a1, va, vb, x[4], nib;
    zip4(wm[0], wm[1], wm[2], wm[3], x); split(x, dbl, rk & 1 && ks != twice && ks != twice2, a0, a1, nib, va, vb);
    uint2* const frag = (uint2*)(g_afrag + (rb >> 2) * (KSTEPS + 2) * 128 + (rb & 3) * 32 + lane) + e;
    frag[ks * 256] = make_uint2(a0, a1);
    if (ks == (twice < KSTEPS ? twice : 0)) frag[KSTEPS * 256] = twice < KSTEPS ? make_uint2(__byte_perm(va, vb, 0x5410), __byte_perm(va, vb, 0x7632)) : make_uint2(0, 0);
    if (ks == twice2) frag[(KSTEPS + 1) * 256] = make_uint2(__byte_perm(va, vb, 0x5410), __byte_perm(va, vb, 0x7632));
    nib <<= 4 * q;
    nib |= __shfl_xor_sync(~0u, nib, 1);
    nib |= __shfl_xor_sync(~0u, nib, 2);
    if (q == 2 * (ks & 1) + e) aux[((ks >> 3) * 32 + lane) * 4 + ((ks >> 1) & 3)] = nib;
    const int em = min(ne, max(8, 16 - no)), om = min(no, 16 - em);
    const int odd = q & 1, m = odd ? om : em;
    auto place = [&](int k) {
        const int t = 15 - k;
        return k >= m ? 16 + (odd ? ne - em : 0) + k - m : k < 8 ? (k >> 1) * 4 + 2 * odd + (k & 1) : (t >> 1) * 4 + 2 * (odd ^ 1) + (t & 1);
    };
    const uint32_t second = (__ballot_sync(~0u, vb != 0) & (0x11111111u << q)) != 0 && !dbl;
    if ((gm >> g) & 1) {
        const int sl = place(rk);
        put_slot(sl >> 2, r * 4 + (sl & 3), !dbl ? va | vb : (rk & 1) ? vb : va, resid_off(ks * 8 + g, rk & 1, r) | (second << 15));
        if (dbl) { const int s2 = place(rk + 1); put_slot(s2 >> 2, r * 4 + (s2 & 3), (rk & 1) ? va : vb, resid_off(ks * 8 + g, ~rk & 1, r)); }
    }
    const int ntot = ne + no, z = 2 * ks + e;
    const int ng = ntot > 16 ? (ntot + 3) >> 2 : min(4, (max(ne, no) + 1) >> 1);
    if (z == 8) {
        const int ulo = units & 7, uhi = (units >> 4) & 7;
        aux[(2 * 32 + lane) * 4 + 1] = ng | (units << 8);
        *(uint2*)(aux + (2 * 32 + lane) * 4 + 2) = make_uint2(__shfl_sync(~0u, ulo < 4 ? b0 : b1, (ulo * 8 + r) & 31) * 0x10001u, __shfl_sync(~0u, uhi < 4 ? b0 : b1, (uhi * 8 + r) & 31) * 0x10001u);
        aux[(3 * 32 + lane) * 4 + 3] = 0; *(uint2*)(aux + (5 * 32 + lane) * 4 + 2) = make_uint2(0, 0);
    }
    const int idx = 2 * z + (q & 1);
    const int frow = z < 6 ? z : z == 6 ? ng - 1 : ng;
    const bool fill = z < 4 ? !(idx < ((q >> 1) ? om : em) || (15 - idx) < ((q >> 1) ? em : om))
                            : (z < 6 || (ng > 6 && (z == 6 || (z == 7 && (ng & 1))))) && 4 * frow + q >= ntot;
    if (fill) put_slot(frow, lane, 0, resid_off(q >> 1, q & 1, r));
}

template<int SEL> __device__ __forceinline__ void wgmma_sp(float (&d)[NACC], const uint32_t (&a)[4], uint64_t bdesc, uint32_t meta) {
    asm volatile("{\n.reg .pred p;\nsetp.ne.b32 p, %22, 0;\n"
        "wgmma.mma_async.sp.sync.aligned.m64n32k32.f32.bf16.bf16 {%0, %1, %2, %3, %4, %5, %6, %7, %8, %9, %10, %11, %12, %13, %14, %15}, {%16, %17, %18, %19}, %20, %21, %23, p, 1, 1, 0;\n}\n"
        : "+f"(d[0]), "+f"(d[1]), "+f"(d[2]), "+f"(d[3]), "+f"(d[4]), "+f"(d[5]), "+f"(d[6]), "+f"(d[7]), "+f"(d[8]), "+f"(d[9]), "+f"(d[10]), "+f"(d[11]), "+f"(d[12]), "+f"(d[13]), "+f"(d[14]), "+f"(d[15])
        : "r"(a[0]), "r"(a[1]), "r"(a[2]), "r"(a[3]), "l"(bdesc), "r"(meta), "r"(1), "n"(SEL));
}

__device__ __forceinline__ void mbar_init(uint32_t bar, uint32_t cnt) { asm volatile("mbarrier.init.shared::cta.b64 [%0], %1;" :: "r"(bar), "r"(cnt) : "memory"); }
__device__ __forceinline__ void mbar_expect_tx(uint32_t bar, uint32_t bytes) {
    asm volatile("mbarrier.arrive.expect_tx.shared::cta.b64 _, [%0], %1;" :: "r"(bar), "r"(bytes) : "memory");
}
__device__ __forceinline__ void mbar_arrive(uint32_t bar) { asm volatile("mbarrier.arrive.shared::cta.b64 _, [%0];" :: "r"(bar) : "memory"); }
__device__ __forceinline__ void mbar_arrive_cluster(uint32_t bar) { asm volatile("mbarrier.arrive.shared::cluster.b64 _, [%0];" :: "r"(bar) : "memory"); }
__device__ __forceinline__ bool mbar_try(uint32_t bar, uint32_t parity) {
    uint32_t ok;
    asm volatile("{\n.reg .pred p;\nmbarrier.try_wait.parity.shared::cta.b64 p, [%1], %2;\nselp.u32 %0, 1, 0, p;\n}\n" : "=r"(ok) : "r"(bar), "r"(parity) : "memory");
    return ok;
}
__device__ __forceinline__ bool mbar_test(uint32_t bar, uint32_t parity) {
    uint32_t ok;
    asm volatile("{\n.reg .pred p;\nmbarrier.test_wait.parity.shared::cta.b64 p, [%1], %2;\nselp.u32 %0, 1, 0, p;\n}\n" : "=r"(ok) : "r"(bar), "r"(parity) : "memory");
    return ok;
}
__device__ __forceinline__ void fail_if(bool c) { asm volatile("{\n.reg .pred p;\nsetp.ne.u32 p, %0, 0;\n@p st.volatile.global.u32 [%1], %0;\n}\n" :: "r"((uint32_t)c), "l"(0ull) : "memory"); }
__device__ __forceinline__ void mbar_wait(uint32_t bar, uint32_t parity) {
    int n = 0;
    while (!mbar_try(bar, parity)) fail_if(++n > (1 << 20));
}
__device__ __forceinline__ void st_async(uint32_t addr, uint32_t v, uint32_t bar) {
    asm volatile("st.async.weak.shared::cluster.mbarrier::complete_tx::bytes.u32 [%0], %1, [%2];" :: "r"(addr), "r"(v), "r"(bar) : "memory");
}
__device__ __forceinline__ uint32_t mapa(uint32_t a, uint32_t cta) { uint32_t d; asm("mapa.shared::cluster.u32 %0, %1, %2;" : "=r"(d) : "r"(a), "r"(cta)); return d; }
__device__ __forceinline__ uint32_t lds32(uint32_t a) { uint32_t v; asm volatile("ld.shared.b32 %0, [%1];" : "=r"(v) : "r"(a)); return v; }
__device__ __forceinline__ uint32_t lds32v(uint32_t a) { uint32_t v; asm volatile("ld.volatile.shared.b32 %0, [%1];" : "=r"(v) : "r"(a) : "memory"); return v; }
__device__ __forceinline__ void sts32(uint32_t a, uint32_t v) { asm volatile("st.shared.b32 [%0], %1;" :: "r"(a), "r"(v) : "memory"); }
__device__ __forceinline__ uint4 ldw(const uint4* a) { uint4 v; asm volatile("ld.weak.global.L1::no_allocate.v4.u32 {%0,%1,%2,%3}, [%4];" : "=r"(v.x), "=r"(v.y), "=r"(v.z), "=r"(v.w) : "l"(a) : "memory"); return v; }
__device__ __forceinline__ void mma_k8(float* c, uint2 a, uint32_t b) {
    asm volatile("mma.sync.aligned.m16n8k8.row.col.f32.bf16.bf16.f32 {%0,%1,%2,%3}, {%4,%5}, {%6}, {%0,%1,%2,%3};"
                 : "+f"(c[0]), "+f"(c[1]), "+f"(c[2]), "+f"(c[3]) : "r"(a.x), "r"(a.y), "r"(b));
}
__device__ __forceinline__ void mma_k16(float* d, uint2 a, uint2 a2, uint32_t b0, uint32_t b1, float c0, float c1, float c2, float c3) {
    asm volatile("mma.sync.aligned.m16n8k16.row.col.f32.bf16.bf16.f32 {%0,%1,%2,%3}, {%4,%5,%6,%7}, {%8,%9}, {%10,%11,%12,%13};"
                 : "=f"(d[0]), "=f"(d[1]), "=f"(d[2]), "=f"(d[3]) : "r"(a.x), "r"(a.y), "r"(a2.x), "r"(a2.y), "r"(b0), "r"(b1), "f"(c0), "f"(c1), "f"(c2), "f"(c3));
}
__device__ __forceinline__ uint32_t pack_bias(float lo, float hi, uint32_t bias2) {
    uint32_t p, o;
    asm("cvt.rn.bf16x2.f32 %0, %1, %2;" : "=r"(p) : "f"(hi), "f"(lo));
    asm("add.rn.bf16x2 %0, %1, %2;" : "=r"(o) : "r"(p), "r"(bias2));
    return o;
}

template <int N> struct Num { static constexpr int value = N; };
struct Params {
    const uint16_t* w; const uint16_t* bias; const uint8_t* x;
    int nq, npages;
    int ncl, nh;
    int nctas;
    int tb, ta, te, slope0, slope1, c0;
    int m0;
    uint32_t ratio[8]; int rm[8];
};
struct Maps { CUtensorMap x[2], o[2], pf; };
__device__ __forceinline__ uint4 entry_w(int M, int w, int q, int extra) {
    const int r = M - ((M + 32) >> 6), o = (r * 9363) >> 16, t = r - 7 * o, odd = t & 1, n = t >> 1;
    const int u = w ^ o ^ odd;
    const int C = 8 * o + 2 * n + ((n ^ u) & 1), C2 = 8 * o + 6 + ((1 ^ u) & 1);
    const uint32_t ra = 57 * C - ((C * 7282) >> 16) + 4 * odd, rb = odd ? 57 * C2 - ((C2 * 7282) >> 16) + 4 + 2 * n : ra + 12;
    const uint32_t rm = 2048 * (2 * (M >> 6) + w) + 56;
    const bool mixed = (M & 63) == 31;
    return make_uint4(M | (mixed << 14) | (q << 17) | (extra << 18), mixed ? rm * 0x10001u + (512u << 16) : ra * 0x10001u + (2u << 16),
                      mixed ? rm * 0x10001u + (1024u | 1536u << 16) : (ra + (odd ? 4 : 10)) | (rb << 16), 0);
}
__device__ __forceinline__ uint4 entry(int M, int q, int extra, unsigned long long plan) {
    const int r = M - ((M + 32) >> 6), page = (r * 2341) >> 16;
    return entry_w(M, (M & 63) == 31 ? q : q ^ (int)((plan >> page) & 1), q, extra);
}
__device__ __forceinline__ int frontier(const Params& p, int t) {
    t = max(t, p.tb);
    const int l = t < p.ta ? LEAD0 + ((p.slope0 * (t - p.tb)) >> 16) : LEADE + max(0, (p.slope1 * (p.te - t)) >> 16);
    return (min(p.nq, t + l) * 9) >> 3;
}
__device__ __forceinline__ uint4 cl_entry(const Params& p, int m, int q, uint32_t ratio, unsigned long long plan) {
    const int nb = (m * ratio + 0x8000u) >> 16, nb1 = m ? ((m - 1) * ratio + 0x8000u) >> 16 : 0;
    uint4 e = entry(p.m0 + m + nb, q, nb - nb1, plan);
    const int c0 = frontier(p, p.m0 + m - 1 + nb1);
    e.w = c0 | (frontier(p, p.m0 + m + nb) - c0) << 16;
    return e;
}
__device__ __forceinline__ int helpers(const Params& p, unsigned long long plan, int q) {
    const int h0 = min(max(((p.ncl + p.nh) >> 1) - (p.ncl - (int)((plan >> 48) & 0xFF)), 0), p.nh);
    return q ? p.nh - h0 : h0;
}
__device__ __forceinline__ void draw(uint32_t& v, uint32_t* ctr, uint32_t inc) {
    asm volatile("{\n.reg .pred p;\nelect.sync _|p, 0xffffffff;\n@p atom.relaxed.gpu.global.add.u32 %0, [%1], %2;\n}" : "+r"(v) : "l"(ctr), "r"(inc) : "memory");
}
__device__ __forceinline__ uint4 lds128v(uint32_t a) { uint4 v; asm volatile("ld.volatile.shared.v4.b32 {%0,%1,%2,%3}, [%4];" : "=r"(v.x), "=r"(v.y), "=r"(v.z), "=r"(v.w) : "r"(a) : "memory"); return v; }
__device__ __forceinline__ void sts128(uint32_t a, uint4 e) { asm volatile("st.shared.v4.b32 [%0], {%1,%2,%3,%4};" :: "r"(a), "r"(e.x), "r"(e.y), "r"(e.z), "r"(e.w) : "memory"); }

__device__ __forceinline__ const uint8_t* probe_line(const Params& p, int page, int cell, int line, int parity) {
    return p.x + ((size_t)page << 21) + cell * 65536 + ((__popc(cell & 0xB) ^ parity) & 1) * 4096 + line * 128;
}
__device__ __forceinline__ int lag(const uint8_t* first, const uint8_t* second, uint32_t scratch, uint32_t since) {
    uint32_t t0, t1;
#pragma unroll 1
    for (int e = 0; e < 2; e++) {
        uint32_t a = 0, b = 0;
        asm volatile("{\n.reg .pred p;\nsetp.ne.s32 p, %4, 0;\n@p ld.global.cg.u32 %0, [%2];\n@p ld.global.cg.u32 %1, [%3];\n}"
                     : "+r"(a), "+r"(b) : "l"(first), "l"(second), "r"(e) : "memory");
        asm volatile("st.volatile.shared.u32 [%0], %1;" :: "r"(scratch), "r"(a) : "memory");
        asm volatile("mov.u32 %0, %%clock;" : "=r"(t0) :: "memory");
        asm volatile("st.volatile.shared.u32 [%0], %1;" :: "r"(scratch), "r"(b) : "memory");
        asm volatile("mov.u32 %0, %%clock;" : "=r"(t1) :: "memory");
        uint32_t t = t1;
        while (t - since < PWAIT) asm volatile("mov.u32 %0, %%clock;" : "=r"(t) :: "memory");
    }
    return t1 - t0;
}

template <bool HELPER>
__global__ void __launch_bounds__(NTHREADS, 1)
spgemm_kernel(const __grid_constant__ Params p, const __grid_constant__ Maps maps) {
    extern __shared__ unsigned char smem_raw[];
    const uint32_t sb = ((uint32_t)__cvta_generic_to_shared(smem_raw) + 1023u) & ~1023u;
    const int tid = threadIdx.x, warp = __shfl_sync(~0u, tid >> 5, 0), lane = tid & 31;
    const int rank = blockIdx.x % CL, cid = blockIdx.x / CL;
    const uint32_t bar_full = sb + OFF_FULL, bar_empty = sb + OFF_EMPTY, tk = sb + OFF_TK;
    const int pr = HELPER ? 2 : rank, pc = HELPER ? blockIdx.x : cid;
    const uint8_t* pl = probe_line(p, pr == 1 ? min(pc, p.npages - 1) : p.npages - 1, pr == 1 ? 30 : pc & 31,
                                   (pr == 1 ? 4 + 2 * max(pc + 1 - p.npages, 0) : pr * 15 + (pc >> 5) * 2) + (warp & 1), warp & 1);
    uint32_t tp;
    asm volatile("mov.u32 %0, %%clock;" : "=r"(tp) :: "memory");
    if (!HELPER && warp >= 14 && lane < 2) asm volatile("prefetch.global.L2 [%0];" :: "l"((const uint8_t*)((uintptr_t)pl ^ (lane << 12))) : "memory");
    uint4 wv[4];
    const int wrow = warp * 16 + (lane & 3) * 4;
    uint32_t b0, b1;
    auto prep_load = [&](int mtile) {
        b0 = __ldg(p.bias + mtile * 64 + lane); b1 = __ldg(p.bias + mtile * 64 + 32 + lane);
#pragma unroll
        for (int j = 0; j < 4; j++) wv[j] = __ldg((const uint4*)(p.w + (rank * 192 + wrow + j) * D + mtile * 64 + (lane >> 2) * 8));
    };
    if (!HELPER && warp < 12) {
        if (cid < 36) prep_load(cid >> 2);
        asm volatile("barrier.cluster.arrive.relaxed.aligned;" ::: "memory");
    }

    if (warp >= 12) {
        asm volatile("setmaxnreg.dec.sync.aligned.u32 32;");
        if (tid == NCONS) {
#pragma unroll
            for (int s = 0; s < NSLOT; s++) { mbar_init(bar_full + 8 * s, 1); mbar_init(bar_empty + 8 * s, HELPER ? 3 : 3 * CL); }
#pragma unroll
            for (int j = 0; j < 8; j++) sts32(tk + 16 * j, 0);
            mbar_init(sb + OFF_MBAR, 1); mbar_init(sb + OFF_MBAR + 8, 1);
            mbar_init(sb + OFF_GO, HELPER ? 12 : 12 + CL); mbar_init(sb + OFF_PLAN, 1); mbar_init(sb + OFF_PLAN2, 1);
            asm volatile("fence.mbarrier_init.release.cluster;" ::: "memory");
            mbar_expect_tx(sb + OFF_MBAR, 36 * 8);
            if (!HELPER && rank != 0) mbar_expect_tx(sb + OFF_PLAN, 16);
        }
        if (tid == NCONS + 32) {
            asm volatile("prefetch.tensormap [%0];" :: "l"(&maps.x[0]) : "memory");
            if (!HELPER) asm volatile("griddepcontrol.launch_dependents;");
            asm volatile("prefetch.tensormap [%0];" :: "l"(&maps.pf) : "memory");
            asm volatile("prefetch.tensormap [%0];" :: "l"(&maps.x[1]) : "memory");
#pragma unroll
            for (int j = 0; j < 2; j++) asm volatile("prefetch.tensormap [%0];" :: "l"(&maps.o[j]) : "memory");
        }
        __syncwarp();
        auto wait_plan = [&]() -> uint4 {
            unsigned long long a, b; int n = 0;
            do { asm volatile("ld.relaxed.gpu.global.v2.u64 {%0, %1}, [%2];" : "=l"(a), "=l"(b) : "l"(&g_plan) : "memory"); fail_if(++n > (1 << 22)); }
            while (__any_sync(~0u, (int)(a >> 56) + (int)(b >> 56) != 2 * p.ncl));
            b &= (1ull << 56) - 1;
            const int side = (b >> cid) & 1, n1 = __popcll(b), below = __popcll(b & ((1ull << cid) - 1));
            a = ((a ^ b) & ((1ull << 40) - 1)) | (unsigned long long)n1 << 48;
            return make_uint4((uint32_t)a, (uint32_t)(a >> 32), side | (side ? below : cid - below) << 8 | (side ? n1 : p.ncl - n1) << 16, 0);
        };
        auto measure = [&](uint32_t since) -> int {
            const int d = lag(pl, (const uint8_t*)((uintptr_t)pl ^ 4096), sb + OFF_INFO + 16 + 4 * (warp & 1), since);
            if (warp == 14 && lane == 0) sts32(sb + OFF_INFO + 24, d);
            asm volatile("bar.sync 11, 64;" ::: "memory");
            return d > (int)lds32v(sb + OFF_INFO + 24);
        };
        uint4 e0 = make_uint4(0, 0, 0, 0), e1 = e0;
        if (HELPER) {
            asm volatile("bar.sync 0;" ::: "memory");
            int side = 0;
            if (warp >= 14) side = measure(tp - PWAIT);
            if (warp == 15) {
                uint32_t old = 0;
                if (lane == 0) {
                    old = atomicAdd(&g_hreg[rank * 32], side ? 0x10000u : 1u);
                    if ((old & 0xFFFF) + (old >> 16) == p.nh - 1) g_hreg[rank * 32] = 0;
                }
                const uint4 inf = wait_plan();
                const unsigned long long plan = inf.x | ((unsigned long long)inf.y << 32);
                old = __shfl_sync(~0u, old, 0);
                int idx = side ? p.nh - 1 - (old >> 16) : old & 0xFFFF, nh = helpers(p, plan, 0), q = 0;
                if (idx >= nh) { idx -= nh; nh = p.nh - nh; q ^= 1; }
                const uint32_t ratio = p.ratio[nh];
                const int rm = p.rm[nh], H = p.nq - p.m0 - rm;
                for (int j0 = 0; __any_sync(~0u, idx + (j0 - 1) * nh < H); j0 += 32) {
                    const int k = idx + (j0 + lane) * nh, mk = (((k + 1) << 16) - 0x8000u + ratio - 1) / ratio;
                    uint4 e = entry(p.m0 + min(mk, rm) + k, q, 0, plan);
                    if (k >= H) e.x = NO_TILE;
                    sts128(sb + OFF_TAB + 16 * (j0 + lane), e);
                }
                __syncwarp();
                if (lane == 0) mbar_arrive(sb + OFF_PLAN);
            }
        } else {
            asm volatile("barrier.cluster.arrive.relaxed.aligned;" ::: "memory");
            if (warp == 12) { e0 = entry_w(cid, 0, 0, 0); e1 = entry_w(cid, 1, 1, 0); }
            if (rank < 2 && warp >= 14) {
                const int side = measure(tp);
                if (warp == 15 && lane == 0) asm volatile("red.relaxed.gpu.global.add.u64 [%0], %1;" :: "l"(rank ? &g_plan.x : &g_plan.y), "l"((1ull << 56) | (unsigned long long)side << cid) : "memory");
            }
            asm volatile("barrier.cluster.wait.aligned;" ::: "memory");
            if (warp >= 13) {
                if (warp == 15 && rank == 0) {
                    const uint4 inf = wait_plan();
                    if (lane == 0) sts128(sb + OFF_INFO, inf);
                    else if (lane < CL)
                        asm volatile("st.async.weak.shared::cluster.mbarrier::complete_tx::bytes.v4.u32 [%0], {%1, %2, %3, %4}, [%5];"
                                     :: "r"(mapa(sb + OFF_INFO, lane)), "r"(inf.x), "r"(inf.y), "r"(inf.z), "r"(inf.w), "r"(mapa(sb + OFF_PLAN, lane)) : "memory");
                }
                if (rank == 0) asm volatile("bar.sync 15, 96;" ::: "memory"); else mbar_wait(sb + OFF_PLAN, 0);
                const uint4 inf = lds128v(sb + OFF_INFO);
                const unsigned long long plan = inf.x | ((unsigned long long)inf.y << 32);
                const int nh = helpers(p, plan, inf.z & 1), rm = p.rm[nh], nc = inf.z >> 16;
                const uint32_t ratio = p.ratio[nh];
                if (warp == 15 && rank == 0) {
                    const int m = ((inf.z >> 8) & 0xFF) + min(lane, NSTAT - 1) * nc;
                    sts128(sb + OFF_TAB + 16 * m, cl_entry(p, m, inf.z & 1, ratio, plan));
                    __syncwarp();
                    if (lane == 0) { mbar_arrive(sb + OFF_PLAN); mbar_expect_tx(sb + OFF_PLAN2, 16 * (rm - NSTAT * nc)); }
                }
                const uint32_t rtab = mapa(sb + OFF_TAB, 0), rbar = mapa(sb + OFF_PLAN2, 0);
                for (int m0 = NSTAT * nc + 96 * (2 - rank); __any_sync(~0u, m0 < rm); m0 += 288) {
                    const int m = m0 + tid - (NCONS + 32);
                    const uint4 e = cl_entry(p, m, inf.z & 1, ratio, plan);
                    if (m < rm) asm volatile("st.async.weak.shared::cluster.mbarrier::complete_tx::bytes.v4.u32 [%0], {%1, %2, %3, %4}, [%5];"
                                             :: "r"(rtab + 16 * m), "r"(e.x), "r"(e.y), "r"(e.z), "r"(e.w), "r"(rbar) : "memory");
                }
            }
        }
        if (warp == 12) {
            if (!HELPER && rank != 0) {
                mbar_wait(sb + OFF_PLAN, 0);
                const uint4 inf = lds128v(sb + OFF_INFO);
                const unsigned long long plan = inf.x | ((unsigned long long)inf.y << 32);
                auto cell = [&](int c, int q) {
                    const int y = 32 * c - 2 + 4 * ((__popc(c & 0xB) ^ (int)(plan >> (c >> 5)) ^ q) & 1);
                    asm volatile("{\n.reg .pred p;\nelect.sync _|p, 0xffffffff;\n@p cp.async.bulk.prefetch.tensor.3d.L2.global.tile [%0, {%1, %2, %1}];\n}" :: "l"(&maps.pf), "r"(0), "r"(y) : "memory");
                };
                const int fe0 = frontier(p, 0), step = 2 * (inf.z >> 16);
                int u0 = p.c0 + 2 * ((inf.z >> 8) & 0xFF) + rank - 1;
                {
                    uint32_t t, due;
                    asm volatile("mov.u32 %0, %%clock;" : "=r"(due) :: "memory");
                    due += (PACE * (u0 - p.c0)) / step;
                    for (; __any_sync(~0u, u0 < fe0); u0 += step, due += PACE) {
                        do { asm volatile("mov.u32 %0, %%clock;" : "=r"(t) :: "memory"); } while (__any_sync(~0u, (int)(t - due) < 0));
                        cell(u0, inf.z & 1);
                    }
                }
                for (int j = XEARLY + rank - 1;; j += 2) {
                    uint4 v; uint32_t ahead;
                    for (int n = 0; __any_sync(~0u, (ahead = (((v = lds128v(tk + ((j & 7) << 4))).x >> 20) - (j + 1)) & 0xFFF) >= 0x800); n++) {
                        if (__any_sync(~0u, lds32v(tk + (((j - 1) & 7) << 4)) == (NO_TILE | (uint32_t)j << 20))) { v.x = NO_TILE; break; }
                        __nanosleep(100); fail_if(n > (1 << 24));
                    }
                    if (__any_sync(~0u, (v.x & NO_TILE) == NO_TILE)) break;
                    j += __reduce_max_sync(~0u, ahead);
                    for (int u = v.w & 0xFFFF; __any_sync(~0u, u < (v.w & 0xFFFF) + (v.w >> 16)); u++) cell(u, (v.x >> 17) & 1);
                }
            } else {
                const uint32_t rtk = HELPER ? tk : mapa(tk, lane < CL ? lane : 0), rfull = HELPER ? bar_full : mapa(bar_full, lane < CL ? lane : 0);
                int s = 0; uint32_t ph = 1;
                uint64_t pol;
                if (!HELPER) asm volatile("createpolicy.fractional.L2::evict_first.b64 %0, 1.0;" : "=l"(pol));
                else asm volatile("createpolicy.fractional.L2::evict_normal.b64 %0, 1.0;" : "=l"(pol));
                auto request = [&](int j, const uint4& t) {
                    const bool valid = t.x != NO_TILE;
                    const CUtensorMap* tm = &maps.x[(t.x >> 14) & 1];
                    mbar_wait(bar_empty + 8 * s, ph);
                    if (__any_sync(~0u, valid)) {
                        const uint32_t dst = sb + OFF_X + s * TILE_BYTES;
                        if (HELPER)
                            asm volatile("{\n.reg .pred p;\nelect.sync _|p, 0xffffffff;\n"
                                         "@p cp.async.bulk.tensor.4d.shared::cluster.global.mbarrier::complete_tx::bytes.L2::cache_hint [%0], [%4, {%6, %7, %6, %6}], [%5], %11;\n"
                                         "@p cp.async.bulk.tensor.4d.shared::cluster.global.mbarrier::complete_tx::bytes.L2::cache_hint [%1], [%4, {%6, %8, %6, %6}], [%5], %11;\n"
                                         "@p cp.async.bulk.tensor.4d.shared::cluster.global.mbarrier::complete_tx::bytes.L2::cache_hint [%2], [%4, {%6, %9, %6, %6}], [%5], %11;\n"
                                         "@p cp.async.bulk.tensor.4d.shared::cluster.global.mbarrier::complete_tx::bytes.L2::cache_hint [%3], [%4, {%6, %10, %6, %6}], [%5], %11;\n}\n"
                                         :: "r"(dst), "r"(dst + 9216), "r"(dst + 2 * 9216), "r"(dst + 3 * 9216), "l"(tm), "r"(bar_full + 8 * s), "r"(0),
                                            "r"(t.y & 0xFFFF), "r"(t.y >> 16), "r"(t.z & 0xFFFF), "r"(t.z >> 16), "l"(pol) : "memory");
                        else
                            asm volatile("{\n.reg .pred p;\nelect.sync _|p, 0xffffffff;\n"
                                         "@p cp.async.bulk.tensor.4d.shared::cluster.global.mbarrier::complete_tx::bytes.multicast::cluster.L2::cache_hint [%0], [%4, {%6, %7, %6, %6}], [%5], %11, %12;\n"
                                         "@p cp.async.bulk.tensor.4d.shared::cluster.global.mbarrier::complete_tx::bytes.multicast::cluster.L2::cache_hint [%1], [%4, {%6, %8, %6, %6}], [%5], %11, %12;\n"
                                         "@p cp.async.bulk.tensor.4d.shared::cluster.global.mbarrier::complete_tx::bytes.multicast::cluster.L2::cache_hint [%2], [%4, {%6, %9, %6, %6}], [%5], %11, %12;\n"
                                         "@p cp.async.bulk.tensor.4d.shared::cluster.global.mbarrier::complete_tx::bytes.multicast::cluster.L2::cache_hint [%3], [%4, {%6, %10, %6, %6}], [%5], %11, %12;\n}\n"
                                         :: "r"(dst), "r"(dst + 9216), "r"(dst + 2 * 9216), "r"(dst + 3 * 9216), "l"(tm), "r"(bar_full + 8 * s), "r"(0),
                                            "r"(t.y & 0xFFFF), "r"(t.y >> 16), "r"(t.z & 0xFFFF), "r"(t.z >> 16), "h"((uint16_t)((1u << CL) - 1)), "l"(pol) : "memory");
                    }
                    if (HELPER) {
                        if (lane == 0) { sts128(tk + ((j & 7) << 4), t); mbar_expect_tx(bar_full + 8 * s, valid ? TILE_BYTES : 0); }
                    } else if (lane < CL) {
                        asm volatile("mbarrier.arrive.expect_tx.shared::cluster.b64 _, [%0], %1;" :: "r"(rfull + 8 * s), "r"(valid ? TILE_BYTES + 16 : 16) : "memory");
                        asm volatile("st.async.weak.shared::cluster.mbarrier::complete_tx::bytes.v4.u32 [%0], {%1, %2, %3, %4}, [%5];"
                                     :: "r"(rtk + ((j & 7) << 4)), "r"(t.x | ((uint32_t)(j + 1) << 20)), "r"(t.y), "r"(t.z), "r"(t.w), "r"(rfull + 8 * s) : "memory");
                    }
                    if (++s == NSLOT) { s = 0; ph ^= 1; }
                };
                if (HELPER) {
#pragma unroll 1
                    for (int j = 0; j < XEARLY; j++) request(j, entry_w(p.ncl + cid + (j >> 1) * (p.ncl + p.nh), j & 1, j & 1, 0));
                    mbar_wait(sb + OFF_PLAN, 0);
                    mbar_wait(sb + OFF_GO, 0);
                    for (int j = XEARLY;; j++) {
                        const uint4 t = lds128v(sb + OFF_TAB + 16 * (j - XEARLY));
                        request(j, t);
                        if (__any_sync(~0u, t.x == NO_TILE)) break;
                    }
                } else {
                    static_assert(XEARLY == 2, "");
                    request(0, e0);
                    request(1, e1);
                    mbar_wait(sb + OFF_PLAN, 0);
                    const uint4 inf = lds128v(sb + OFF_INFO);
                    const unsigned long long plan = inf.x | ((unsigned long long)inf.y << 32);
                    const int side = inf.z & 1, nc = inf.z >> 16;
                    const int nh = helpers(p, plan, side), rm = p.rm[nh], rmo = p.rm[p.nh - nh];
                    const uint32_t ratio = p.ratio[nh], ratioo = p.ratio[p.nh - nh];
                    const int st = NSTAT * nc, sto = NSTAT * (p.ncl - nc);
                    uint4 t = lds128v(sb + OFF_TAB + 16 * ((inf.z >> 8) & 0xFF));
                    mbar_wait(sb + OFF_GO, 0);
                    int j = XEARLY;
#pragma unroll 1
                    for (; j < XEARLY + NSTAT - 2; j++) {
                        const uint4 tn = lds128v(sb + OFF_TAB + 16 * (((inf.z >> 8) & 0xFF) + (j + 1 - XEARLY) * nc));
                        request(j, t);
                        t = tn;
                    }
                    uint32_t drawn = 0;
                    int q = side;
                    request(j++, t);
                    draw(drawn, &g_ticket, 1u << (16 * side));
                    t = lds128v(sb + OFF_TAB + 16 * (((inf.z >> 8) & 0xFF) + (NSTAT - 1) * nc));
                    mbar_wait(sb + OFF_PLAN2, 0);
                    for (;; j++) {
                        request(j, t);
                        uint32_t v = __reduce_max_sync(~0u, drawn);
                        int m = st + ((v >> (16 * side)) & 0xFFFF), mo = sto + ((v >> (16 - 16 * side)) & 0xFFFF);
                        if (q == side ? m >= rm && mo < rmo : mo >= rmo && m < rm) {
                            q ^= 1;
                            draw(drawn, &g_ticket, 1u << (16 * q));
                            v = __reduce_max_sync(~0u, drawn);
                            m = st + ((v >> (16 * side)) & 0xFFFF); mo = sto + ((v >> (16 - 16 * side)) & 0xFFFF);
                        }
                        if (q == side ? m >= rm : mo >= rmo) break;
                        const bool own = q == side;
                        q = m + ((m * ratio) >> 16) > mo + ((mo * ratioo) >> 16) + DELTA ? side ^ 1 : side;
                        draw(drawn, &g_ticket, 1u << (16 * q));
                        if (own) t = lds128v(sb + OFF_TAB + 16 * m);
                        else t = cl_entry(p, mo, side ^ 1, ratioo, plan);
                    }
                    t.x = NO_TILE;
                    request(j + 1, t);
                    if (lane == 0 && atomicInc(&g_done, p.ncl - 1) == (uint32_t)p.ncl - 1) g_ticket = 0;
                }
            }
        } else {
            const int g = warp - 13;
            uint64_t spol;
            asm volatile("createpolicy.fractional.L2::evict_first.b64 %0, 1.0;" : "=l"(spol));
            mbar_wait(sb + OFF_GO, 0);
            if (g == 2 && lane == 0 && atomicInc(&g_passed, p.nctas - 1) == (uint32_t)p.nctas - 1) {
#pragma unroll
                for (int m = 0; m < 36; m++) g_ready[m * 32] = 0;
                g_plan = make_ulonglong2(0, 0);
            }
            __syncwarp();
            for (int i = 0;; i++) {
                asm volatile("bar.arrive %0, 160;" :: "r"(12 + g) : "memory");
                asm volatile("bar.sync %0, 160;" :: "r"(1 + g) : "memory");
                const uint4 t = lds128v(tk + ((i & 7) << 4));
                if ((t.x & NO_TILE) == NO_TILE) break;
                const CUtensorMap* tm = &maps.o[(t.x >> 14) & 1];
                const int row[4] = {(int)(t.y & 0xFFFF), (int)(t.y >> 16), (int)(t.z & 0xFFFF), (int)(t.z >> 16)};
                if (lane == 0) {
#pragma unroll
                    for (int k = 0; k < 4; k++)
                        asm volatile("cp.async.bulk.tensor.3d.global.shared::cta.bulk_group.L2::cache_hint [%0, {%2, %3, %4}], [%1], %5;"
                                     :: "l"(tm), "r"(sb + OFF_STG + (g + 3 * (i & 1)) * STG_BYTES + k * 1024), "r"((g * 3 + rank) * 64), "r"(row[k]), "r"(0), "l"(spol) : "memory");
                    asm volatile("cp.async.bulk.commit_group;" ::: "memory");
                    asm volatile("cp.async.bulk.wait_group.read 1;" ::: "memory");
                }
                __syncwarp();
            }
            if (lane == 0) asm volatile("cp.async.bulk.wait_group.read 0;" ::: "memory");
        }
        __syncwarp();
        if (!HELPER) asm volatile("barrier.cluster.arrive.relaxed.aligned;\nbarrier.cluster.wait.aligned;" ::: "memory");
    } else {
        asm volatile("setmaxnreg.inc.sync.aligned.u32 160;");
        const int wg = warp >> 2, wtid = tid & 127;
        if (HELPER) asm volatile("bar.sync 0;" ::: "memory");
        else {
            int prb = cid;
            if (prb >= 36) asm volatile("barrier.cluster.wait.aligned;" ::: "memory");
#pragma unroll 1
            for (int round = 0; prb < 36; prb += p.ncl, round++) {
                const uint32_t wsm = sb + OFF_WST, msk = sb + OFF_MSK + (round & 1) * 288, mbar = sb + OFF_MBAR + (round & 1) * 8;
                if (round) {
                    asm volatile("bar.sync 3, 384;" ::: "memory");
                    if (tid == 0) mbar_expect_tx(mbar, 36 * 8);
                    prep_load(prb >> 2);
                }
                const int nt = ties(wv[0].x, wv[1].x, wv[2].x, wv[3].x) + ties(wv[0].y, wv[1].y, wv[2].y, wv[3].y) +
                               ties(wv[0].z, wv[1].z, wv[2].z, wv[3].z) + ties(wv[0].w, wv[1].w, wv[2].w, wv[3].w);
                const uint32_t mk = __ballot_sync(~0u, nt > 0), md = __ballot_sync(~0u, nt > 1);
                if (round == 0) asm volatile("barrier.cluster.wait.aligned;" ::: "memory");
                if (lane < CL)
                    asm volatile("st.async.weak.shared::cluster.mbarrier::complete_tx::bytes.v2.u32 [%0], {%1, %2}, [%3];"
                                 :: "r"(mapa(msk + (rank * 12 + warp) * 8, lane)), "r"(mk), "r"(md), "r"(mapa(mbar, lane)) : "memory");
#pragma unroll
                for (int j = 0; j < 4; j++) {
                    const int row = wrow + j;
                    const uint32_t ad = wsm + row * 128 + (((lane >> 2) ^ ((row & 1) | ((row >> 1) & 6))) << 4);
                    asm volatile("st.shared.v4.b32 [%0], {%1,%2,%3,%4};" :: "r"(ad), "r"(wv[j].x), "r"(wv[j].y), "r"(wv[j].z), "r"(wv[j].w) : "memory");
                }
                if (warp == 0) {
                    mbar_wait(mbar, (round >> 1) & 1);
                    uint4 ms = make_uint4(0, 0, 0, 0);
                    if (lane < KSTEPS) ms = lds128v(msk + 16 * lane);
                    const uint32_t te = (ms.x & 0x0F0F0F0Fu) | ((ms.z & 0x0F0F0F0Fu) << 4), to = ((ms.x >> 4) & 0x0F0F0F0Fu) | (ms.z & 0xF0F0F0F0u);
                    const uint32_t de = (ms.y & 0x0F0F0F0Fu) | ((ms.w & 0x0F0F0F0Fu) << 4), dq = ((ms.y >> 4) & 0x0F0F0F0Fu) | (ms.w & 0xF0F0F0F0u);
                    auto count = [](uint32_t v) { v -= (v >> 1) & 0x55555555u; v = (v & 0x33333333u) + ((v >> 2) & 0x33333333u); return (v + (v >> 4)) & 0x0F0F0F0Fu; };
                    const uint32_t c0 = __reduce_add_sync(~0u, count(te)), c1 = __reduce_add_sync(~0u, count(to));
                    auto byte = [](uint32_t a, uint32_t b, uint32_t u) { return __byte_perm(a, b, (u >> 1) + 4 * (u & 1)) & 0xFFu; };
                    const uint32_t ku = byte(c0, c1, lane & 7) * 8 + (lane & 7), k2 = 2 * (lane >> 3);
                    const uint32_t ranks = __reduce_add_sync(~0u, ((byte(c0, c1, k2) * 8 + k2 < ku) + (byte(c0, c1, k2 + 1) * 8 + k2 + 1 < ku)) << (4 * (lane & 7)));
                    const uint32_t order = __reduce_add_sync(~0u, lane < 8 ? lane << (4 * ((ranks >> (4 * lane)) & 7)) : 0);
                    int cnt[4]; uint32_t mq = 0;
#pragma unroll
                    for (int z = 0; z < 4; z++) {
                        const uint32_t ua = (order >> (4 * z)) & 7, ub = (order >> (28 - 4 * z)) & 7;
                        const uint32_t ta = byte(te, to, ua), tb = byte(te, to, ub), v = ta | tb | ((ta & tb) | byte(de, dq, ua) | byte(de, dq, ub)) << 8;
                        cnt[z] = __popc(v);
                        if (z == (prb & 3)) mq = v;
                    }
                    const uint32_t l01 = __reduce_add_sync(~0u, cnt[0] | cnt[1] << 16), l23 = __reduce_add_sync(~0u, cnt[2] | cnt[3] << 16);
                    const int ulo = (order >> (4 * (prb & 3))) & 7, uhi = (order >> (28 - 4 * (prb & 3))) & 7;
                    const int full = max(max(max((int)(l01 & 0xFFFF) - cnt[0], (int)(l01 >> 16) - cnt[1]), max((int)(l23 & 0xFFFF) - cnt[2], (int)(l23 >> 16) - cnt[3])), 16);
                    const uint32_t more = (65 - cnt[0] - cnt[1] - cnt[2] - cnt[3]) << 5 | lane;
                    const uint32_t best = __reduce_min_sync(~0u, lane < KSTEPS ? full << 12 | more : full << 12 | 31);
                    const int twice = best & 31;
                    int twice2 = 31;
                    if (best >> 12 > 16 && twice < KSTEPS) {
                        const uint32_t r01 = l01 - __shfl_sync(~0u, cnt[0] | cnt[1] << 16, twice), r23 = l23 - __shfl_sync(~0u, cnt[2] | cnt[3] << 16, twice);
                        const int full2 = max(max((int)(r01 & 0xFFFF) - cnt[0], (int)(r01 >> 16) - cnt[1]), max((int)(r23 & 0xFFFF) - cnt[2], (int)(r23 >> 16) - cnt[3]));
                        twice2 = __reduce_min_sync(~0u, lane < KSTEPS && lane != twice ? max(full2, 16) << 12 | more : ~0u) & 31;
                    }
                    sts32(sb + OFF_SEL + 4 * lane, lane == 31 ? ulo | (uhi << 4) | (twice << 8) | (twice2 << 13) : lane == twice || lane == twice2 ? 0 : mq);
                }
                asm volatile("bar.sync 1, 384;" ::: "memory");
                const uint32_t units = lds32v(sb + OFF_SEL + 4 * 31), mq = lds32v(sb + OFF_SEL + 4 * min(lane, 30));
                uint32_t wm[4];
                load_units(wsm, warp, units & 7, (units >> 4) & 7, lane, wm);
                emit_half(wm, mq, prb, rank * 6 + (warp >> 1), warp & 1, lane, units, b0, b1);
                asm volatile("bar.sync 2, 384;" ::: "memory");
                if (tid == 0) asm volatile("red.release.gpu.global.add.u32 [%0], 1;" :: "l"(&g_ready[prb * 32]) : "memory");
            }
            if (warp == 0 && lane < CL) mbar_arrive_cluster(mapa(sb + OFF_GO, lane));
        }
        const int mt = wg * 3 + rank, rb = mt * 4 + (warp & 3);
        {
            uint32_t v; int n = 0;
            do { asm volatile("ld.acquire.gpu.global.u32 %0, [%1];" : "=r"(v) : "l"(&g_ready[rb * 32]) : "memory"); fail_if(++n > (1 << 22)); } while (__any_sync(~0u, v < CL));
        }
        if (wg > 0) asm volatile("bar.sync %0, 256;" :: "r"(7 + wg) : "memory");
        uint32_t a[KSTEPS + 2][4], meta[9];
        uint2 rv[3]; uint32_t ro[3], sel[3];
        uint32_t info, bias_lo, bias_hi;
        {
            const uint4* ap = g_aux + rb * 6 * 32 + lane;
            const uint4 v3 = ldw(ap + 96), v2 = ldw(ap + 64), v4 = ldw(ap + 128), v5 = ldw(ap + 160), v0 = ldw(ap), v1 = ldw(ap + 32);
            meta[0] = v0.x; meta[1] = v0.y; meta[2] = v0.z; meta[3] = v0.w; meta[4] = v1.x; meta[5] = v1.y; meta[6] = v1.z; meta[7] = v1.w;
            meta[8] = v2.x; info = v2.y; bias_lo = v2.z; bias_hi = v2.w;
            ro[0] = v3.x; ro[1] = v3.y; ro[2] = v3.z;
            rv[0] = make_uint2(v4.x, v4.y); rv[1] = make_uint2(v4.z, v4.w); rv[2] = make_uint2(v5.x, v5.y);
        }
#pragma unroll
        for (int k = 0; k < KSTEPS + 1; k++) { uint4 v = ldw(&g_afrag[(mt * (KSTEPS + 2) + k) * 128 + wtid]); a[k][0] = v.x; a[k][1] = v.y; a[k][2] = v.z; a[k][3] = v.w; }
        if (wg < 2) asm volatile("bar.arrive %0, 256;" :: "r"(8 + wg) : "memory");
        if (lane == 0) mbar_arrive(sb + OFF_GO);
        auto selector = [](uint32_t o) { return 0x5410u + ((o >> 15) & 1) * 0x22u + (o >> 31) * 0x2200u; };
#pragma unroll
        for (int j = 0; j < 3; j++) { sel[j] = selector(ro[j]); ro[j] &= 0x7FFF7FFFu; }
        mbar_wait(bar_full, 0);
        info = __shfl_sync(~0u, info, 0);
        const int ngrp = info & 0xFF, ulo = (info >> 8) & 7, uhi = (info >> 12) & 7;
        const uint32_t stg = sb + OFF_STG + wg * STG_BYTES + ((lane >> 4) * 8 + (lane & 7)) * 128 + (((((lane >> 3) & 1) ? uhi : ulo) ^ (lane & 7)) << 4);
        const uint32_t twice = (((info >> 17) & 15) * 1024 + ((info >> 16) & 1) * 64) >> 4;
        const uint32_t twice2 = (((info >> 22) & 15) * 1024 + ((info >> 21) & 1) * 64) >> 4;
        const uint32_t rempty = HELPER ? bar_empty : mapa(bar_empty, 0);
        float acc[NACC];
        uint32_t bq[NB][6];
        auto gather = [&](uint32_t xb) {
#pragma unroll
            for (int j = 0; j < 4; j++) {
                const uint32_t o = xb + ((j & 1) ? ro[j >> 1] >> 16 : ro[j >> 1] & 0xFFFF);
#pragma unroll
                for (int n = 0; n < NB; n++) {
                    if (j < 3) { bq[n][j] = lds32(o + n * 9216); continue; }
                    bq[n][j] = 0;
                    asm volatile("{\n.reg .pred p;\nsetp.lt.s32 p, %2, %3;\n@p ld.shared.b32 %0, [%1];\n}" : "+r"(bq[n][j]) : "r"(o + n * 9216), "r"(j), "r"(ngrp) : "memory");
                }
            }
        };
        auto select = [&]() {
#pragma unroll
            for (int n = 0; n < NB; n++)
#pragma unroll
                for (int j = 0; j < 2; j++) bq[n][2 * j] = __byte_perm(bq[n][2 * j], bq[n][2 * j + 1], sel[j]);
        };
        auto further = [&](uint32_t xb, int bar) {
#pragma unroll 1
            for (int y = 4; y < min(ngrp, 5); y++) {
#pragma unroll
                for (int n = 0; n < NB; n++) { bq[n][4] = lds32(xb + (ro[2] & 0xFFFF) + n * 9216); bq[n][5] = lds32(xb + (ro[2] >> 16) + n * 9216); }
#pragma unroll
                for (int n = 0; n < NB; n++) mma_k8(acc + 4 * n, rv[2], __byte_perm(bq[n][4], bq[n][5], sel[2]));
                if (bar >= 0) asm volatile("bar.arrive %0, 256;" :: "r"(bar) : "memory");
#pragma unroll 1
                for (int z = 3; 2 * z < ngrp; z++) {
                    const uint2 v = __ldca(&g_rval[(rb * 36 + z) * 32 + lane]); const uint32_t off = __ldca(&g_roff[(rb * 36 + z) * 32 + lane]);
                    uint32_t bx[NB];
#pragma unroll
                    for (int n = 0; n < NB; n++) bx[n] = __byte_perm(lds32(xb + (off & 0x7FFF) + n * 9216), lds32(xb + ((off >> 16) & 0x7FFF) + n * 9216), selector(off));
#pragma unroll
                    for (int n = 0; n < NB; n++) mma_k8(acc + 4 * n, v, bx[n]);
                }
            }
        };
        bool more = true;
#pragma unroll
        for (int n = 0; n < NB; n++) bq[n][4] = bq[n][5] = 0;
        gather(sb + OFF_X);
        select();
#pragma unroll
        for (int n = 0; n < NB; n++) mma_k16(acc + 4 * n, rv[0], rv[1], bq[n][0], bq[n][2], 0.f, 0.f, 0.f, 0.f);
        further(sb + OFF_X, -1);
        const int bar_a = 8 + wg, bar_an = 8 + (wg + 2) % 3, bar_tn = 4 + (wg + 2) % 3;
        if (wg == 1) asm volatile("bar.arrive 4, 256;" ::: "memory");
        if (wg == 2) { asm volatile("bar.sync 10, 256;" ::: "memory"); asm volatile("bar.arrive 5, 256;" ::: "memory"); }
        auto run = [&](auto tw) {
        constexpr int TW = decltype(tw)::value;
        int s = 0; uint32_t ph = 0;
        bool ready = false;
        for (int i = 0; more; i++) {
            const uint32_t xb = sb + OFF_X + s * TILE_BYTES;
            const int s1 = s + 1 == NSLOT ? 0 : s + 1;
            const uint32_t ph1 = s1 == 0 ? ph ^ 1 : ph;
            asm volatile("bar.sync %0, 256;" :: "r"(4 + wg) : "memory");
            const uint64_t desc = ((uint64_t)1 << 62) | ((uint64_t)(9216 >> 4) << 32) | ((uint64_t)1 << 16) | (uint64_t)(xb >> 4);
            asm volatile("wgmma.fence.sync.aligned;" ::: "memory");
#pragma unroll
            for (int k = 0; k < KSTEPS; k++) {
                const uint64_t d = desc + (uint64_t)(((k >> 1) * 1024 + (k & 1) * 64) >> 4);
                if (k & 1) wgmma_sp<1>(acc, a[k], d, meta[k >> 1]);
                else       wgmma_sp<0>(acc, a[k], d, meta[k >> 1]);
            }
            if (TW > 0) wgmma_sp<0>(acc, a[KSTEPS], desc + twice, 0x44444444u);
            if (TW > 1) wgmma_sp<0>(acc, a[KSTEPS + 1], desc + twice2, 0x44444444u);
            asm volatile("wgmma.commit_group.sync.aligned;" ::: "memory");
            asm volatile("bar.arrive %0, 256;" :: "r"(bar_an) : "memory");
            if (!ready) mbar_wait(bar_full + 8 * s1, ph1);
            const uint32_t tn = lds32v(tk + (((i + 1) & 7) << 4));
            gather(sb + OFF_X + s1 * TILE_BYTES);
            asm volatile("bar.sync %0, 160;" :: "r"(12 + wg) : "memory");
            asm volatile("wgmma.wait_group.sync.aligned 0;" ::: "memory");
            const uint32_t sg = stg + (i & 1) * (3 * STG_BYTES);
            if (wtid == 0) { if (HELPER) mbar_arrive(bar_empty + 8 * s); else mbar_arrive_cluster(rempty + 8 * s); }
#pragma unroll
            for (int n = 0; n < NB; n += 2) {
                const uint32_t p0 = pack_bias(acc[4 * n], acc[4 * n + 1], bias_lo), p1 = pack_bias(acc[4 * n + 2], acc[4 * n + 3], bias_hi);
                const uint32_t p2 = pack_bias(acc[4 * n + 4], acc[4 * n + 5], bias_lo), p3 = pack_bias(acc[4 * n + 6], acc[4 * n + 7], bias_hi);
                if (n == 0) asm volatile("stmatrix.sync.aligned.m8n8.x4.trans.shared.b16 [%0], {%1,%2,%3,%4};" :: "r"(sg + n * 1024), "r"(p0), "r"(p1), "r"(p2), "r"(p3) : "memory");
                else asm volatile("{\n.reg .pred p;\nAGAIN:\nstmatrix.sync.aligned.m8n8.x4.trans.shared.b16 [%0], {%1,%2,%3,%4};\nsetp.eq.u32 p, %5, 0xFFFFFFFE;\n@p bra.uni AGAIN;\n}"
                                  :: "r"(sg + n * 1024), "r"(p0), "r"(p1), "r"(p2), "r"(p3), "r"(info) : "memory");
            }
            more = __any_sync(~0u, (tn & NO_TILE) != NO_TILE);
            select();
            if (wg != 2 || more) {
                asm volatile("{\n.reg .pred p;\nTURN:\nbar.sync %0, 256;\nsetp.eq.u32 p, %1, 0xFFFFFFFF;\n@p bra.uni TURN;\n}" :: "r"(bar_a), "r"(info) : "memory");
#pragma unroll
                for (int n = 0; n < NB; n++) {
                    mma_k16(acc + 4 * n, rv[0], rv[1], bq[n][0], bq[n][2], 0.f, 0.f, 0.f, 0.f);
                    if (n == 0) asm volatile("{\n.reg .pred p;\nsetp.le.s32 p, %1, 4;\n@p bar.arrive %0, 256;\n}" :: "r"(bar_tn), "r"(ngrp) : "memory");
                }
                further(sb + OFF_X + s1 * TILE_BYTES, bar_tn);
            }
            asm volatile("fence.proxy.async.shared::cta;" ::: "memory");
            asm volatile("bar.arrive %0, 160;" :: "r"(1 + wg) : "memory");
            s = s1; ph = ph1;
            ready = __all_sync(~0u, mbar_test(bar_full + 8 * (s + 1 == NSLOT ? 0 : s + 1), s + 1 == NSLOT ? ph ^ 1 : ph));
        }
        };
        if (((info >> 16) & 31) >= KSTEPS) run(Num<0>());
        else if (((info >> 21) & 31) >= KSTEPS) run(Num<1>());
        else {
            const uint4 v = ldw(&g_afrag[(mt * (KSTEPS + 2) + KSTEPS + 1) * 128 + wtid]);
            a[KSTEPS + 1][0] = v.x; a[KSTEPS + 1][1] = v.y; a[KSTEPS + 1][2] = v.z; a[KSTEPS + 1][3] = v.w;
            run(Num<2>());
        }
        if (wg == 0) asm volatile("bar.sync 4, 256;" ::: "memory");
        asm volatile("bar.sync %0, 160;" :: "r"(12 + wg) : "memory");
        asm volatile("bar.arrive %0, 160;" :: "r"(1 + wg) : "memory");
        if (!HELPER) asm volatile("barrier.cluster.arrive.relaxed.aligned;\nbarrier.cluster.wait.aligned;" ::: "memory");
    }
}

typedef CUresult (*EncodeFn)(CUtensorMap*, CUtensorMapDataType, cuuint32_t, void*, const cuuint64_t*, const cuuint64_t*, const cuuint32_t*, const cuuint32_t*,
                             CUtensorMapInterleave, CUtensorMapSwizzle, CUtensorMapL2promotion, CUtensorMapFloatOOBfill);

__global__ void plain_kernel(const __nv_bfloat16* x, const __nv_bfloat16* w, const __nv_bfloat16* b, __nv_bfloat16* out, int ntok) {
    const int t0 = blockIdx.x * 8;
    for (int f = threadIdx.x; f < D; f += blockDim.x) {
        float acc[8] = {};
        for (int g = 0; g < D / 4; g++) {
            float v[4], m[4];
            for (int i = 0; i < 4; i++) { v[i] = __bfloat162float(w[(4 * g + i) * D + f]); m[i] = fabsf(v[i]); }
            const float thr = fmaxf(fminf(fmaxf(m[0], m[1]), fmaxf(m[2], m[3])), fmaxf(fminf(m[0], m[1]), fminf(m[2], m[3])));
            for (int i = 0; i < 4; i++)
                for (int t = 0; t < 8; t++)
                    if (m[i] >= thr && t0 + t < ntok) acc[t] += v[i] * __bfloat162float(x[(size_t)(t0 + t) * D + 4 * g + i]);
        }
        for (int t = 0; t < 8; t++)
            if (t0 + t < ntok) out[(size_t)(t0 + t) * D + f] = __hadd(__float2bfloat16(acc[t]), b[f]);
    }
}

extern "C" void kernel_launch(void* const* d_in, const int* in_sizes, int n_in, void* d_out, int out_size) {
    static EncodeFn enc = nullptr;
    static int ncl = 0, nhelp = 0;
    const int ntok = in_sizes[0] / D;
    cudaLaunchConfig_t cfg = {};
    cudaLaunchAttribute at[1];
    at[0].id = cudaLaunchAttributeClusterDimension; at[0].val.clusterDim.x = CL; at[0].val.clusterDim.y = 1; at[0].val.clusterDim.z = 1;
    cfg.blockDim = dim3(NTHREADS); cfg.dynamicSmemBytes = SMEM_BYTES; cfg.attrs = at; cfg.numAttrs = 1; cfg.stream = cudaStreamPerThread;
    if (!enc) {
        cudaDriverEntryPointQueryResult qr; void* fn = nullptr;
        cudaGetDriverEntryPoint("cuTensorMapEncodeTiled", &fn, cudaEnableDefault, &qr);
        enc = (EncodeFn)fn;
        cudaFuncSetAttribute(spgemm_kernel<false>, cudaFuncAttributeMaxDynamicSharedMemorySize, SMEM_BYTES);
        cudaFuncSetAttribute(spgemm_kernel<true>, cudaFuncAttributeMaxDynamicSharedMemorySize, SMEM_BYTES);
        int dev = 0, nsm = 0;
        cudaGetDevice(&dev);
        cudaDeviceGetAttribute(&nsm, cudaDevAttrMultiProcessorCount, dev);
        cfg.gridDim = dim3(CL * (nsm / CL));
        cudaOccupancyMaxActiveClusters(&ncl, spgemm_kernel<false>, &cfg);
        if (ncl < 1) ncl = 1;
        nhelp = nsm > CL * ncl ? (nsm - CL * ncl) / CL : 0;
        if (nhelp > 7) nhelp = 7;
    }
    if (ntok % 4096 || ntok < 16384 || ntok > 65536 || ncl < 2 || ncl > 56 || ncl < CL * nhelp || 8 * (ncl + nhelp) > ntok / 64) {
        plain_kernel<<<(ntok + 7) / 8, 192, 0, cudaStreamPerThread>>>((const __nv_bfloat16*)d_in[0], (const __nv_bfloat16*)d_in[1], (const __nv_bfloat16*)d_in[2], (__nv_bfloat16*)d_out, ntok);
        return;
    }
    Maps maps;
    for (int v = 0; v < 2; v++) {
        const cuuint32_t rows = v == 0 ? 2 : 1;
        const cuuint64_t pitch = (v == 0 ? 14 : 57) * D * 2;
        {
            cuuint64_t dims[4] = {64, (cuuint64_t)ntok, 8 / rows, 9};
            cuuint64_t strides[3] = {D * 2, pitch, 128};
            cuuint32_t box[4] = {64, rows, 8 / rows, 9}, es[4] = {1, 1, 1, 1};
            enc(&maps.x[v], CU_TENSOR_MAP_DATA_TYPE_BFLOAT16, 4, d_in[0], dims, strides, box, es, CU_TENSOR_MAP_INTERLEAVE_NONE,
                CU_TENSOR_MAP_SWIZZLE_128B, CU_TENSOR_MAP_L2_PROMOTION_L2_128B, CU_TENSOR_MAP_FLOAT_OOB_FILL_NONE);
        }
        {
            cuuint64_t dims[3] = {D, (cuuint64_t)ntok, 8 / rows};
            cuuint64_t strides[2] = {D * 2, pitch};
            cuuint32_t box[3] = {64, rows, 8 / rows}, es[3] = {1, 1, 1};
            enc(&maps.o[v], CU_TENSOR_MAP_DATA_TYPE_BFLOAT16, 3, d_out, dims, strides, box, es, CU_TENSOR_MAP_INTERLEAVE_NONE,
                CU_TENSOR_MAP_SWIZZLE_128B, CU_TENSOR_MAP_L2_PROMOTION_NONE, CU_TENSOR_MAP_FLOAT_OOB_FILL_NONE);
        }
    }
    {
        cuuint64_t dims[3] = {256, (cuuint64_t)ntok * D * 2 / 2048, 4};
        cuuint64_t strides[2] = {2048, 16384};
        cuuint32_t box[3] = {256, 4, 4}, es[3] = {1, 1, 1};
        enc(&maps.pf, CU_TENSOR_MAP_DATA_TYPE_FLOAT64, 3, d_in[0], dims, strides, box, es, CU_TENSOR_MAP_INTERLEAVE_NONE,
            CU_TENSOR_MAP_SWIZZLE_NONE, CU_TENSOR_MAP_L2_PROMOTION_NONE, CU_TENSOR_MAP_FLOAT_OOB_FILL_NONE);
    }
    Params p;
    p.w = (const uint16_t*)d_in[1]; p.bias = (const uint16_t*)d_in[2]; p.x = (const uint8_t*)d_in[0];
    p.nq = ntok / 64; p.npages = (int)(((size_t)ntok * D * 2) >> 21);
    const int nc = ncl, nh = nhelp;
    p.ncl = nc; p.nh = nh; p.nctas = CL * (nc + nh);
    p.m0 = (nc + nh) * XEARLY / 2;
    for (int h = 0; h < 8; h++) {
        const uint32_t R = p.nq - p.m0, H = h * (HT * p.nq / 1024 * 44 / (nc + nh));
        p.ratio[h] = h <= nh ? (H << 16) / (R - H) : 0;
        p.rm[h] = p.ratio[h] ? (((R - 1) << 16) + 0x7FFFu) / (0x10000u + p.ratio[h]) + 1 : R;
    }
    p.c0 = (p.m0 * 9) >> 3;
    p.tb = p.m0 + (NSLOT - XEARLY) * (nc + nh) / 2;
    p.ta = p.tb + 1 + (int)((p.nq - p.tb) * TAFRAC); p.te = (int)(p.nq * TEFRAC) + 2;
    p.slope0 = ((LEAD1 - LEAD0) << 16) / (p.ta - p.tb); p.slope1 = ((LEAD1 - LEADE) << 16) / (p.te - p.ta);
    cfg.gridDim = dim3(CL * nc);
    cudaLaunchKernelEx(&cfg, spgemm_kernel<false>, p, maps);
    if (nh) {
        at[0].id = cudaLaunchAttributeProgrammaticStreamSerialization; at[0].val.programmaticStreamSerializationAllowed = 1;
        cfg.gridDim = dim3(CL * nh);
        cudaLaunchKernelEx(&cfg, spgemm_kernel<true>, p, maps);
    }
}
```

```cpp
#include <cuda_runtime.h>
#include <cuda_bf16.h>
#include <cuda.h>
#include <stdint.h>

constexpr int D = 576;
constexpr int NT = 32;
constexpr int NSLOT = 5;
constexpr int XEARLY = 2;
constexpr int NSTAT = 4;
constexpr int DELTA = 36;
constexpr int HT = 45;
constexpr int LEAD0 = 140, LEAD1 = 290, LEADE = 22, PACE = 1200;
constexpr double TAFRAC = 0.249, TEFRAC = 1.0;
constexpr int PWAIT = 1900;
constexpr int KSTEPS = 18;
constexpr int CL = 3;
constexpr int TILE_BYTES = NT * D * 2;
constexpr int STG_BYTES = NT * 128;
constexpr int NACC = NT / 2;
constexpr int NB = NT / 8;
constexpr int NCONS = 384;
constexpr int NTHREADS = 512;
constexpr int NTAB = 1024;
constexpr uint32_t NO_TILE = 0xFFFFFu;

constexpr int OFF_X = 0;
constexpr int OFF_WST = OFF_X + (NSLOT - 1) * TILE_BYTES;
constexpr int OFF_STG = OFF_X + NSLOT * TILE_BYTES;
constexpr int OFF_TAB = OFF_STG + 6 * STG_BYTES;
constexpr int OFF_TK = OFF_TAB + 16 * NTAB;
constexpr int OFF_MSK = OFF_TK + 128;
constexpr int OFF_SEL = OFF_MSK + 2 * 36 * 8;
constexpr int OFF_INFO = OFF_SEL + 128;
constexpr int OFF_FULL = OFF_INFO + 32;
constexpr int OFF_EMPTY = OFF_FULL + 8 * NSLOT;
constexpr int OFF_MBAR = OFF_EMPTY + 8 * NSLOT;
constexpr int OFF_GO = OFF_MBAR + 16;
constexpr int OFF_PLAN = OFF_GO + 8;
constexpr int OFF_PLAN2 = OFF_PLAN + 8;
constexpr int SMEM_BYTES = OFF_PLAN2 + 8 + 1024;
static_assert(SMEM_BYTES <= 232448 && TILE_BYTES >= 192 * 128 && XEARLY % 2 == 0 && XEARLY < NSLOT && NSLOT < 8 && NB == 4 && OFF_INFO % 16 == 0, "layout");

__device__ __align__(128) uint4    g_afrag[9 * (KSTEPS + 2) * 128];
__device__ __align__(128) uint4    g_aux[36 * 6 * 32];
__device__ __align__(128) uint2    g_rval[36 * 36 * 32];
__device__ __align__(128) uint32_t g_roff[36 * 36 * 32];
__device__ __align__(128) uint32_t g_ready[36 * 32];
__device__ __align__(128) uint32_t g_passed;
__device__ __align__(128) uint32_t g_ticket;
__device__ __align__(128) uint32_t g_hreg[3 * 32];
__device__ __align__(128) uint32_t g_done;
__device__ __align__(128) ulonglong2 g_plan;

__device__ __forceinline__ uint32_t max2(uint32_t a, uint32_t b) { uint32_t d; asm("max.u16x2 %0, %1, %2;" : "=r"(d) : "r"(a), "r"(b)); return d; }
__device__ __forceinline__ uint32_t min2(uint32_t a, uint32_t b) { uint32_t d; asm("min.u16x2 %0, %1, %2;" : "=r"(d) : "r"(a), "r"(b)); return d; }
__device__ __forceinline__ uint32_t sign2(uint32_t a) { uint32_t d; asm("prmt.b32 %0, %1, %1, 0xBB99;" : "=r"(d) : "r"(a)); return d; }
__device__ __forceinline__ void load_units(uint32_t wsm, int g4, int ulo, int uhi, int lane, uint32_t (&m)[4]) {
    const int row = g4 * 16 + ((lane & 7) >> 1) * 4 + ((lane >> 3) & 1) * 2 + (lane & 1);
    const uint32_t ad = wsm + row * 128 + (((lane < 16 ? ulo : uhi) ^ ((row & 1) | ((row >> 1) & 6))) << 4);
    asm volatile("ldmatrix.sync.aligned.m8n8.x4.trans.shared.b16 {%0,%1,%2,%3}, [%4];" : "=r"(m[0]), "=r"(m[1]), "=r"(m[2]), "=r"(m[3]) : "r"(ad) : "memory");
}
__device__ __forceinline__ void zip4(uint32_t a01, uint32_t a23, uint32_t b01, uint32_t b23, uint32_t (&x)[4]) {
    x[0] = __byte_perm(a01, b01, 0x5410); x[1] = __byte_perm(a01, b01, 0x7632); x[2] = __byte_perm(a23, b23, 0x5410); x[3] = __byte_perm(a23, b23, 0x7632);
}
__device__ __forceinline__ void middle2(const uint32_t (&x)[4], uint32_t (&m)[4], uint32_t& u, uint32_t& v) {
#pragma unroll
    for (int i = 0; i < 4; i++) m[i] = x[i] & 0x7FFF7FFFu;
    u = min2(max2(m[0], m[1]), max2(m[2], m[3])); v = max2(min2(m[0], m[1]), min2(m[2], m[3]));
}
__device__ __forceinline__ int ties(uint32_t x0, uint32_t x1, uint32_t x2, uint32_t x3) {
    const uint32_t x[4] = {x0, x1, x2, x3};
    uint32_t m[4], u, v;
    middle2(x, m, u, v);
    const uint32_t t = u ^ v, f = u ^ min2(min2(m[0], m[1]), min2(m[2], m[3]));
    const bool t0 = (t & 0xFFFFu) == 0 && (v & 0xFFFFu) != 0, t1 = t < 0x10000u && v >= 0x10000u;
    return t0 + t1 + 2 * ((t0 && (f & 0xFFFFu) == 0) || (t1 && f < 0x10000u));
}
__device__ __forceinline__ void split(const uint32_t (&x)[4], bool dbl, bool P, uint32_t& alo, uint32_t& ahi, uint32_t& nib, uint32_t& va, uint32_t& vb) {
    uint32_t m[4], u, v;
    middle2(x, m, u, v);
    const uint32_t c = 0x80008000u - max2(max2(u, v), 0x00010001u);
    uint32_t k0 = sign2(m[0] + c), k1 = sign2(m[1] + c), k2 = sign2(m[2] + c), k3 = sign2(m[3] + c);
    const uint32_t three = (k0 & k1 & (k2 | k3)) | (k2 & k3 & (k0 | k1)), four = k0 & k1 & k2 & k3;
    const bool a2 = !dbl && P;
    const uint32_t pa = a2 ? k2 : k0, pb = dbl ? k2 : P ? k3 : k1;
    const uint32_t ra = three & pa, rb = three & pb & (four | ~pa);
    va = (a2 ? x[2] : x[0]) & ra; vb = (dbl ? x[2] : P ? x[3] : x[1]) & rb;
    if (a2) k2 &= ~ra; else k0 &= ~ra;
    if (dbl) k2 &= ~rb; else if (P) k3 &= ~rb; else k1 &= ~rb;
    const uint32_t s1 = k1 & k0, s2 = k2 & (k0 | k1);
    const uint32_t t = (k1 & x[1]) | (~k1 & k2 & x[2]);
    const uint32_t x0 = (k0 & x[0]) | (~k0 & t), x1 = (s1 & x[1]) | (s2 & x[2]) | (k3 & x[3]);
    nib = (~k0 & k1 & 0x00010001u) | (~k0 & ~k1 & 0x00020002u) | (~s2 & 0x00040004u) | (~s1 & 0x00080008u);
    alo = __byte_perm(x0, x1, 0x5410); ahi = __byte_perm(x0, x1, 0x7632);
}
__device__ __forceinline__ uint32_t resid_off(int g, int P, int r) {
    int k0 = 4 * g + 2 * P;
    int chunk = k0 >> 6, byte = (k0 & 63) * 2;
    return chunk * 1024 + r * 128 + (((byte >> 4) ^ r) << 4) + (byte & 15);
}
__device__ __forceinline__ void emit_half(const uint32_t (&wm)[4], uint32_t md, int rb, int ks, int e, int lane, uint32_t units, uint32_t b0, uint32_t b1) {
    uint32_t* const aux = (uint32_t*)(g_aux + rb * 6 * 32);
    auto put_slot = [&](int j, int ln, uint32_t v, uint32_t off) {
        uint16_t* o = j < 6 ? (uint16_t*)aux + (3 * 32 + ln) * 8 + j : (uint16_t*)g_roff + ((rb * 36 + (j >> 1)) * 32 + ln) * 2 + (j & 1);
        uint16_t* w = j < 6 ? (uint16_t*)aux + ((4 + (j >> 2)) * 32 + ln) * 8 + (j & 2) * 2 + (j & 1) : (uint16_t*)g_rval + ((rb * 36 + (j >> 1)) * 32 + ln) * 4 + (j & 1);
        o[0] = (uint16_t)off; w[0] = (uint16_t)v; w[2] = (uint16_t)(v >> 16);
    };
    const int r = lane >> 2, q = lane & 3, g = 4 * e + q, twice = (units >> 8) & 31, twice2 = units >> 13;
    const uint32_t gm = __shfl_sync(~0u, md, ks);
    const uint32_t c2 = __popc(md & 0x5555u) | (__popc(md & 0xAAAAu) << 16);
    const uint32_t tot = __reduce_add_sync(~0u, c2), pre = __reduce_add_sync(~0u, lane < ks ? c2 : 0u);
    const int ne = tot & 0xFFFF, no = tot >> 16;
    const int rk = ((q & 1) ? pre >> 16 : pre & 0xFFFF) + __popc(gm & ((q & 1) ? 0xAAAAu : 0x5555u) & (((1u << g) - 1) * 0x101u));
    const bool dbl = (gm >> (8 + g)) & 1;
    uint32_t a0, a1, va, vb, x[4], nib;
    zip4(wm[0], wm[1], wm[2], wm[3], x); split(x, dbl, rk & 1 && ks != twice && ks != twice2, a0, a1, nib, va, vb);
    uint2* const frag = (uint2*)(g_afrag + (rb >> 2) * (KSTEPS + 2) * 128 + (rb & 3) * 32 + lane) + e;
    frag[ks * 256] = make_uint2(a0, a1);
    if (ks == (twice < KSTEPS ? twice : 0)) frag[KSTEPS * 256] = twice < KSTEPS ? make_uint2(__byte_perm(va, vb, 0x5410), __byte_perm(va, vb, 0x7632)) : make_uint2(0, 0);
    if (ks == twice2) frag[(KSTEPS + 1) * 256] = make_uint2(__byte_perm(va, vb, 0x5410), __byte_perm(va, vb, 0x7632));
    nib <<= 4 * q;
    nib |= __shfl_xor_sync(~0u, nib, 1);
    nib |= __shfl_xor_sync(~0u, nib, 2);
    if (q == 2 * (ks & 1) + e) aux[((ks >> 3) * 32 + lane) * 4 + ((ks >> 1) & 3)] = nib;
    const int em = min(ne, max(8, 16 - no)), om = min(no, 16 - em);
    const int odd = q & 1, m = odd ? om : em;
    auto place = [&](int k) {
        const int t = 15 - k;
        return k >= m ? 16 + (odd ? ne - em : 0) + k - m : k < 8 ? (k >> 1) * 4 + 2 * odd + (k & 1) : (t >> 1) * 4 + 2 * (odd ^ 1) + (t & 1);
    };
    const uint32_t second = (__ballot_sync(~0u, vb != 0) & (0x11111111u << q)) != 0 && !dbl;
    if ((gm >> g) & 1) {
        const int sl = place(rk);
        put_slot(sl >> 2, r * 4 + (sl & 3), !dbl ? va | vb : (rk & 1) ? vb : va, resid_off(ks * 8 + g, rk & 1, r) | (second << 15));
        if (dbl) { const int s2 = place(rk + 1); put_slot(s2 >> 2, r * 4 + (s2 & 3), (rk & 1) ? va : vb, resid_off(ks * 8 + g, ~rk & 1, r)); }
    }
    const int ntot = ne + no, z = 2 * ks + e;
    const int ng = ntot > 16 ? (ntot + 3) >> 2 : min(4, (max(ne, no) + 1) >> 1);
    if (z == 8) {
        const int ulo = units & 7, uhi = (units >> 4) & 7;
        aux[(2 * 32 + lane) * 4 + 1] = ng | (units << 8);
        *(uint2*)(aux + (2 * 32 + lane) * 4 + 2) = make_uint2(__shfl_sync(~0u, ulo < 4 ? b0 : b1, (ulo * 8 + r) & 31) * 0x10001u, __shfl_sync(~0u, uhi < 4 ? b0 : b1, (uhi * 8 + r) & 31) * 0x10001u);
        aux[(3 * 32 + lane) * 4 + 3] = 0; *(uint2*)(aux + (5 * 32 + lane) * 4 + 2) = make_uint2(0, 0);
    }
    const int idx = 2 * z + (q & 1);
    const int frow = z < 6 ? z : z == 6 ? ng - 1 : ng;
    const bool fill = z < 4 ? !(idx < ((q >> 1) ? om : em) || (15 - idx) < ((q >> 1) ? em : om))
                            : (z < 6 || (ng > 6 && (z == 6 || (z == 7 && (ng & 1))))) && 4 * frow + q >= ntot;
    if (fill) put_slot(frow, lane, 0, resid_off(q >> 1, q & 1, r));
}

template<int SEL> __device__ __forceinline__ void wgmma_sp(float (&d)[NACC], const uint32_t (&a)[4], uint64_t bdesc, uint32_t meta) {
    asm volatile("{\n.reg .pred p;\nsetp.ne.b32 p, %22, 0;\n"
        "wgmma.mma_async.sp.sync.aligned.m64n32k32.f32.bf16.bf16 {%0, %1, %2, %3, %4, %5, %6, %7, %8, %9, %10, %11, %12, %13, %14, %15}, {%16, %17, %18, %19}, %20, %21, %23, p, 1, 1, 0;\n}\n"
        : "+f"(d[0]), "+f"(d[1]), "+f"(d[2]), "+f"(d[3]), "+f"(d[4]), "+f"(d[5]), "+f"(d[6]), "+f"(d[7]), "+f"(d[8]), "+f"(d[9]), "+f"(d[10]), "+f"(d[11]), "+f"(d[12]), "+f"(d[13]), "+f"(d[14]), "+f"(d[15])
        : "r"(a[0]), "r"(a[1]), "r"(a[2]), "r"(a[3]), "l"(bdesc), "r"(meta), "r"(1), "n"(SEL));
}

__device__ __forceinline__ void mbar_init(uint32_t bar, uint32_t cnt) { asm volatile("mbarrier.init.shared::cta.b64 [%0], %1;" :: "r"(bar), "r"(cnt) : "memory"); }
__device__ __forceinline__ void mbar_expect_tx(uint32_t bar, uint32_t bytes) {
    asm volatile("mbarrier.arrive.expect_tx.shared::cta.b64 _, [%0], %1;" :: "r"(bar), "r"(bytes) : "memory");
}
__device__ __forceinline__ void mbar_arrive(uint32_t bar) { asm volatile("mbarrier.arrive.shared::cta.b64 _, [%0];" :: "r"(bar) : "memory"); }
__device__ __forceinline__ void mbar_arrive_cluster(uint32_t bar) { asm volatile("mbarrier.arrive.shared::cluster.b64 _, [%0];" :: "r"(bar) : "memory"); }
__device__ __forceinline__ bool mbar_try(uint32_t bar, uint32_t parity) {
    uint32_t ok;
    asm volatile("{\n.reg .pred p;\nmbarrier.try_wait.parity.shared::cta.b64 p, [%1], %2;\nselp.u32 %0, 1, 0, p;\n}\n" : "=r"(ok) : "r"(bar), "r"(parity) : "memory");
    return ok;
}
__device__ __forceinline__ bool mbar_test(uint32_t bar, uint32_t parity) {
    uint32_t ok;
    asm volatile("{\n.reg .pred p;\nmbarrier.test_wait.parity.shared::cta.b64 p, [%1], %2;\nselp.u32 %0, 1, 0, p;\n}\n" : "=r"(ok) : "r"(bar), "r"(parity) : "memory");
    return ok;
}
__device__ __forceinline__ void fail_if(bool c) { asm volatile("{\n.reg .pred p;\nsetp.ne.u32 p, %0, 0;\n@p st.volatile.global.u32 [%1], %0;\n}\n" :: "r"((uint32_t)c), "l"(0ull) : "memory"); }
__device__ __forceinline__ void mbar_wait(uint32_t bar, uint32_t parity) {
    int n = 0;
    while (!mbar_try(bar, parity)) fail_if(++n > (1 << 20));
}
__device__ __forceinline__ void st_async(uint32_t addr, uint32_t v, uint32_t bar) {
    asm volatile("st.async.weak.shared::cluster.mbarrier::complete_tx::bytes.u32 [%0], %1, [%2];" :: "r"(addr), "r"(v), "r"(bar) : "memory");
}
__device__ __forceinline__ uint32_t mapa(uint32_t a, uint32_t cta) { uint32_t d; asm("mapa.shared::cluster.u32 %0, %1, %2;" : "=r"(d) : "r"(a), "r"(cta)); return d; }
__device__ __forceinline__ uint32_t lds32(uint32_t a) { uint32_t v; asm volatile("ld.shared.b32 %0, [%1];" : "=r"(v) : "r"(a)); return v; }
__device__ __forceinline__ uint32_t lds32v(uint32_t a) { uint32_t v; asm volatile("ld.volatile.shared.b32 %0, [%1];" : "=r"(v) : "r"(a) : "memory"); return v; }
__device__ __forceinline__ void sts32(uint32_t a, uint32_t v) { asm volatile("st.shared.b32 [%0], %1;" :: "r"(a), "r"(v) : "memory"); }
__device__ __forceinline__ uint4 ldw(const uint4* a) { uint4 v; asm volatile("ld.weak.global.L1::no_allocate.v4.u32 {%0,%1,%2,%3}, [%4];" : "=r"(v.x), "=r"(v.y), "=r"(v.z), "=r"(v.w) : "l"(a) : "memory"); return v; }
__device__ __forceinline__ void mma_k8(float* c, uint2 a, uint32_t b) {
    asm volatile("mma.sync.aligned.m16n8k8.row.col.f32.bf16.bf16.f32 {%0,%1,%2,%3}, {%4,%5}, {%6}, {%0,%1,%2,%3};"
                 : "+f"(c[0]), "+f"(c[1]), "+f"(c[2]), "+f"(c[3]) : "r"(a.x), "r"(a.y), "r"(b));
}
__device__ __forceinline__ void mma_k16(float* d, uint2 a, uint2 a2, uint32_t b0, uint32_t b1, float c0, float c1, float c2, float c3) {
    asm volatile("mma.sync.aligned.m16n8k16.row.col.f32.bf16.bf16.f32 {%0,%1,%2,%3}, {%4,%5,%6,%7}, {%8,%9}, {%10,%11,%12,%13};"
                 : "=f"(d[0]), "=f"(d[1]), "=f"(d[2]), "=f"(d[3]) : "r"(a.x), "r"(a.y), "r"(a2.x), "r"(a2.y), "r"(b0), "r"(b1), "f"(c0), "f"(c1), "f"(c2), "f"(c3));
}
__device__ __forceinline__ uint32_t pack_bias(float lo, float hi, uint32_t bias2) {
    uint32_t p, o;
    asm("cvt.rn.bf16x2.f32 %0, %1, %2;" : "=r"(p) : "f"(hi), "f"(lo));
    asm("add.rn.bf16x2 %0, %1, %2;" : "=r"(o) : "r"(p), "r"(bias2));
    return o;
}

template <int N> struct Num { static constexpr int value = N; };
struct Params {
    const uint16_t* w; const uint16_t* bias; const uint8_t* x;
    int nq, npages;
    int rot, wrap;
    int ncl, nh;
    int nctas;
    int tb, ta, te, slope0, slope1, c0;
    int m0;
    uint32_t ratio[8]; int rm[8];
};
struct Maps { CUtensorMap x[2], o[2], pf; };
__device__ __forceinline__ int octet(const Params& p, int v) { return v < p.wrap ? v + 9 * p.rot : v - p.wrap; }
__device__ __forceinline__ uint4 entry_w(const Params& p, int M, int w, int q, int extra) {
    const int r = M - ((M + 32) >> 6), v = (r * 9363) >> 16, o = octet(p, v), t = r - 7 * v, odd = t & 1, n = t >> 1;
    const int u = w ^ o ^ odd;
    const int C = 8 * o + 2 * n + ((n ^ u) & 1), C2 = 8 * o + 6 + ((1 ^ u) & 1);
    const uint32_t ra = 57 * C - ((C * 7282) >> 16) + 4 * odd, rb = odd ? 57 * C2 - ((C2 * 7282) >> 16) + 4 + 2 * n : ra + 12;
    const uint32_t rm = 2048 * (2 * ((o * 7282) >> 16) + w) + 56;
    const bool mixed = (M & 63) == 31;
    return make_uint4(M | (mixed << 14) | (q << 17) | (extra << 18), mixed ? rm * 0x10001u + (512u << 16) : ra * 0x10001u + (2u << 16),
                      mixed ? rm * 0x10001u + (1024u | 1536u << 16) : (ra + (odd ? 4 : 10)) | (rb << 16), 0);
}
__device__ __forceinline__ uint4 entry(const Params& p, int M, int q, int extra, unsigned long long plan) {
    const int page = octet(p, ((M - ((M + 32) >> 6)) * 9363) >> 16) >> 2;
    return entry_w(p, M, (M & 63) == 31 ? q : q ^ (int)((plan >> page) & 1), q, extra);
}
__device__ __forceinline__ int frontier(const Params& p, int t) {
    t = max(t, p.tb);
    const int l = t < p.ta ? LEAD0 + ((p.slope0 * (t - p.tb)) >> 16) : LEADE + max(0, (p.slope1 * (p.te - t)) >> 16);
    return (min(p.nq, t + l) * 9) >> 3;
}
__device__ __forceinline__ uint4 cl_entry(const Params& p, int m, int q, uint32_t ratio, unsigned long long plan) {
    const int nb = (m * ratio + 0x8000u) >> 16, nb1 = m ? ((m - 1) * ratio + 0x8000u) >> 16 : 0;
    uint4 e = entry(p, p.m0 + m + nb, q, nb - nb1, plan);
    const int c0 = frontier(p, p.m0 + m - 1 + nb1);
    e.w = c0 | (frontier(p, p.m0 + m + nb) - c0) << 16;
    return e;
}
__device__ __forceinline__ int helpers(const Params& p, unsigned long long plan, int q) {
    const int h0 = min(max(((p.ncl + p.nh) >> 1) - (p.ncl - (int)((plan >> 48) & 0xFF)), 0), p.nh);
    return q ? p.nh - h0 : h0;
}
__device__ __forceinline__ void draw(uint32_t& v, uint32_t* ctr, uint32_t inc) {
    asm volatile("{\n.reg .pred p;\nelect.sync _|p, 0xffffffff;\n@p atom.relaxed.gpu.global.add.u32 %0, [%1], %2;\n}" : "+r"(v) : "l"(ctr), "r"(inc) : "memory");
}
__device__ __forceinline__ uint4 lds128v(uint32_t a) { uint4 v; asm volatile("ld.volatile.shared.v4.b32 {%0,%1,%2,%3}, [%4];" : "=r"(v.x), "=r"(v.y), "=r"(v.z), "=r"(v.w) : "r"(a) : "memory"); return v; }
__device__ __forceinline__ void sts128(uint32_t a, uint4 e) { asm volatile("st.shared.v4.b32 [%0], {%1,%2,%3,%4};" :: "r"(a), "r"(e.x), "r"(e.y), "r"(e.z), "r"(e.w) : "memory"); }

__device__ __forceinline__ const uint8_t* probe_line(const Params& p, int page, int cell, int line, int parity) {
    return p.x + ((size_t)page << 21) + cell * 65536 + ((__popc(cell & 0xB) ^ parity) & 1) * 4096 + line * 128;
}
__device__ __forceinline__ int lag(const uint8_t* first, const uint8_t* second, uint32_t scratch, uint32_t since) {
    uint32_t t0, t1;
#pragma unroll 1
    for (int e = 0; e < 2; e++) {
        uint32_t a = 0, b = 0;
        asm volatile("{\n.reg .pred p;\nsetp.ne.s32 p, %4, 0;\n@p ld.global.cg.u32 %0, [%2];\n@p ld.global.cg.u32 %1, [%3];\n}"
                     : "+r"(a), "+r"(b) : "l"(first), "l"(second), "r"(e) : "memory");
        asm volatile("st.volatile.shared.u32 [%0], %1;" :: "r"(scratch), "r"(a) : "memory");
        asm volatile("mov.u32 %0, %%clock;" : "=r"(t0) :: "memory");
        asm volatile("st.volatile.shared.u32 [%0], %1;" :: "r"(scratch), "r"(b) : "memory");
        asm volatile("mov.u32 %0, %%clock;" : "=r"(t1) :: "memory");
        uint32_t t = t1;
        while (t - since < PWAIT) asm volatile("mov.u32 %0, %%clock;" : "=r"(t) :: "memory");
    }
    return t1 - t0;
}

template <bool HELPER>
__global__ void __launch_bounds__(NTHREADS, 1)
spgemm_kernel(const __grid_constant__ Params p, const __grid_constant__ Maps maps) {
    extern __shared__ unsigned char smem_raw[];
    const uint32_t sb = ((uint32_t)__cvta_generic_to_shared(smem_raw) + 1023u) & ~1023u;
    const int tid = threadIdx.x, warp = __shfl_sync(~0u, tid >> 5, 0), lane = tid & 31;
    const int rank = blockIdx.x % CL, cid = blockIdx.x / CL;
    const uint32_t bar_full = sb + OFF_FULL, bar_empty = sb + OFF_EMPTY, tk = sb + OFF_TK;
    const int pr = HELPER ? 2 : rank, pc = HELPER ? blockIdx.x : cid;
    const uint8_t* pl = probe_line(p, pr == 1 ? min(pc, p.npages - 1) : p.npages - 1, pr == 1 ? 30 : pc & 31,
                                   (pr == 1 ? 4 + 2 * max(pc + 1 - p.npages, 0) : pr * 15 + (pc >> 5) * 2) + (warp & 1), warp & 1);
    uint32_t tp;
    asm volatile("mov.u32 %0, %%clock;" : "=r"(tp) :: "memory");
    if (!HELPER && warp >= 14 && lane < 2) asm volatile("prefetch.global.L2 [%0];" :: "l"((const uint8_t*)((uintptr_t)pl ^ (lane << 12))) : "memory");
    uint4 wv[4];
    const int wrow = warp * 16 + (lane & 3) * 4;
    uint32_t b0, b1;
    auto prep_load = [&](int mtile) {
        b0 = __ldg(p.bias + mtile * 64 + lane); b1 = __ldg(p.bias + mtile * 64 + 32 + lane);
#pragma unroll
        for (int j = 0; j < 4; j++) wv[j] = __ldg((const uint4*)(p.w + (rank * 192 + wrow + j) * D + mtile * 64 + (lane >> 2) * 8));
    };
    if (!HELPER && warp < 12) {
        if (cid < 36) prep_load(cid >> 2);
        asm volatile("barrier.cluster.arrive.relaxed.aligned;" ::: "memory");
    }

    if (warp >= 12) {
        asm volatile("setmaxnreg.dec.sync.aligned.u32 32;");
        if (tid == NCONS) {
#pragma unroll
            for (int s = 0; s < NSLOT; s++) { mbar_init(bar_full + 8 * s, 1); mbar_init(bar_empty + 8 * s, HELPER ? 3 : 3 * CL); }
#pragma unroll
            for (int j = 0; j < 8; j++) sts32(tk + 16 * j, 0);
            mbar_init(sb + OFF_MBAR, 1); mbar_init(sb + OFF_MBAR + 8, 1);
            mbar_init(sb + OFF_GO, HELPER ? 12 : 12 + CL); mbar_init(sb + OFF_PLAN, 1); mbar_init(sb + OFF_PLAN2, 1);
            asm volatile("fence.mbarrier_init.release.cluster;" ::: "memory");
            mbar_expect_tx(sb + OFF_MBAR, 36 * 8);
            if (!HELPER && rank != 0) mbar_expect_tx(sb + OFF_PLAN, 16);
        }
        if (tid == NCONS + 32) {
            asm volatile("prefetch.tensormap [%0];" :: "l"(&maps.x[0]) : "memory");
            if (!HELPER) asm volatile("griddepcontrol.launch_dependents;");
            asm volatile("prefetch.tensormap [%0];" :: "l"(&maps.pf) : "memory");
            asm volatile("prefetch.tensormap [%0];" :: "l"(&maps.x[1]) : "memory");
#pragma unroll
            for (int j = 0; j < 2; j++) asm volatile("prefetch.tensormap [%0];" :: "l"(&maps.o[j]) : "memory");
        }
        __syncwarp();
        auto wait_plan = [&]() -> uint4 {
            unsigned long long a, b; int n = 0;
            do { asm volatile("ld.relaxed.gpu.global.v2.u64 {%0, %1}, [%2];" : "=l"(a), "=l"(b) : "l"(&g_plan) : "memory"); fail_if(++n > (1 << 22)); }
            while (__any_sync(~0u, (int)(a >> 56) + (int)(b >> 56) != 2 * p.ncl));
            b &= (1ull << 56) - 1;
            const int side = (b >> cid) & 1, n1 = __popcll(b), below = __popcll(b & ((1ull << cid) - 1));
            a = ((a ^ b) & ((1ull << 40) - 1)) | (unsigned long long)n1 << 48;
            return make_uint4((uint32_t)a, (uint32_t)(a >> 32), side | (side ? below : cid - below) << 8 | (side ? n1 : p.ncl - n1) << 16, 0);
        };
        auto measure = [&](uint32_t since) -> int {
            const int d = lag(pl, (const uint8_t*)((uintptr_t)pl ^ 4096), sb + OFF_INFO + 16 + 4 * (warp & 1), since);
            if (warp == 14 && lane == 0) sts32(sb + OFF_INFO + 24, d);
            asm volatile("bar.sync 11, 64;" ::: "memory");
            return d > (int)lds32v(sb + OFF_INFO + 24);
        };
        uint4 e0 = make_uint4(0, 0, 0, 0), e1 = e0;
        if (HELPER) {
            asm volatile("bar.sync 0;" ::: "memory");
            int side = 0;
            if (warp >= 14) side = measure(tp - PWAIT);
            if (warp == 15) {
                uint32_t old = 0;
                if (lane == 0) {
                    old = atomicAdd(&g_hreg[rank * 32], side ? 0x10000u : 1u);
                    if ((old & 0xFFFF) + (old >> 16) == p.nh - 1) g_hreg[rank * 32] = 0;
                }
                const uint4 inf = wait_plan();
                const unsigned long long plan = inf.x | ((unsigned long long)inf.y << 32);
                old = __shfl_sync(~0u, old, 0);
                int idx = side ? p.nh - 1 - (old >> 16) : old & 0xFFFF, nh = helpers(p, plan, 0), q = 0;
                if (idx >= nh) { idx -= nh; nh = p.nh - nh; q ^= 1; }
                const uint32_t ratio = p.ratio[nh];
                const int rm = p.rm[nh], H = p.nq - p.m0 - rm;
                for (int j0 = 0; __any_sync(~0u, idx + (j0 - 1) * nh < H); j0 += 32) {
                    const int k = idx + (j0 + lane) * nh, mk = (((k + 1) << 16) - 0x8000u + ratio - 1) / ratio;
                    uint4 e = entry(p, p.m0 + min(mk, rm) + k, q, 0, plan);
                    if (k >= H) e.x = NO_TILE;
                    sts128(sb + OFF_TAB + 16 * (j0 + lane), e);
                }
                __syncwarp();
                if (lane == 0) mbar_arrive(sb + OFF_PLAN);
            }
        } else {
            asm volatile("barrier.cluster.arrive.relaxed.aligned;" ::: "memory");
            if (warp == 12) { e0 = entry_w(p, cid, 0, 0, 0); e1 = entry_w(p, cid, 1, 1, 0); }
            if (rank < 2 && warp >= 14) {
                const int side = measure(tp);
                if (warp == 15 && lane == 0) asm volatile("red.relaxed.gpu.global.add.u64 [%0], %1;" :: "l"(rank ? &g_plan.x : &g_plan.y), "l"((1ull << 56) | (unsigned long long)side << cid) : "memory");
            }
            asm volatile("barrier.cluster.wait.aligned;" ::: "memory");
            if (warp >= 13) {
                if (warp == 15 && rank == 0) {
                    const uint4 inf = wait_plan();
                    if (lane == 0) sts128(sb + OFF_INFO, inf);
                    else if (lane < CL)
                        asm volatile("st.async.weak.shared::cluster.mbarrier::complete_tx::bytes.v4.u32 [%0], {%1, %2, %3, %4}, [%5];"
                                     :: "r"(mapa(sb + OFF_INFO, lane)), "r"(inf.x), "r"(inf.y), "r"(inf.z), "r"(inf.w), "r"(mapa(sb + OFF_PLAN, lane)) : "memory");
                }
                if (rank == 0) asm volatile("bar.sync 15, 96;" ::: "memory"); else mbar_wait(sb + OFF_PLAN, 0);
                const uint4 inf = lds128v(sb + OFF_INFO);
                const unsigned long long plan = inf.x | ((unsigned long long)inf.y << 32);
                const int nh = helpers(p, plan, inf.z & 1), rm = p.rm[nh], nc = inf.z >> 16;
                const uint32_t ratio = p.ratio[nh];
                if (warp == 15 && rank == 0) {
                    const int m = ((inf.z >> 8) & 0xFF) + min(lane, NSTAT - 1) * nc;
                    sts128(sb + OFF_TAB + 16 * m, cl_entry(p, m, inf.z & 1, ratio, plan));
                    __syncwarp();
                    if (lane == 0) { mbar_arrive(sb + OFF_PLAN); mbar_expect_tx(sb + OFF_PLAN2, 16 * (rm - NSTAT * nc)); }
                }
                const uint32_t rtab = mapa(sb + OFF_TAB, 0), rbar = mapa(sb + OFF_PLAN2, 0);
                for (int m0 = NSTAT * nc + 96 * (2 - rank); __any_sync(~0u, m0 < rm); m0 += 288) {
                    const int m = m0 + tid - (NCONS + 32);
                    const uint4 e = cl_entry(p, m, inf.z & 1, ratio, plan);
                    if (m < rm) asm volatile("st.async.weak.shared::cluster.mbarrier::complete_tx::bytes.v4.u32 [%0], {%1, %2, %3, %4}, [%5];"
                                             :: "r"(rtab + 16 * m), "r"(e.x), "r"(e.y), "r"(e.z), "r"(e.w), "r"(rbar) : "memory");
                }
            }
        }
        if (warp == 12) {
            if (!HELPER && rank != 0) {
                mbar_wait(sb + OFF_PLAN, 0);
                const uint4 inf = lds128v(sb + OFF_INFO);
                const unsigned long long plan = inf.x | ((unsigned long long)inf.y << 32);
                auto cell = [&](int v, int q) {
                    const int c = 8 * octet(p, v >> 3) + (v & 7);
                    const int y = 32 * c - 2 + 4 * ((__popc(c & 0xB) ^ (int)(plan >> (c >> 5)) ^ q) & 1);
                    asm volatile("{\n.reg .pred p;\nelect.sync _|p, 0xffffffff;\n@p cp.async.bulk.prefetch.tensor.3d.L2.global.tile [%0, {%1, %2, %1}];\n}" :: "l"(&maps.pf), "r"(0), "r"(y) : "memory");
                };
                const int fe0 = frontier(p, 0), step = 2 * (inf.z >> 16);
                int u0 = p.c0 + 2 * ((inf.z >> 8) & 0xFF) + rank - 1;
                {
                    uint32_t t, due;
                    asm volatile("mov.u32 %0, %%clock;" : "=r"(due) :: "memory");
                    due += (PACE * (u0 - p.c0)) / step;
                    for (; __any_sync(~0u, u0 < fe0); u0 += step, due += PACE) {
                        do { asm volatile("mov.u32 %0, %%clock;" : "=r"(t) :: "memory"); } while (__any_sync(~0u, (int)(t - due) < 0));
                        cell(u0, inf.z & 1);
                    }
                }
                for (int j = XEARLY + rank - 1;; j += 2) {
                    uint4 v; uint32_t ahead;
                    for (int n = 0; __any_sync(~0u, (ahead = (((v = lds128v(tk + ((j & 7) << 4))).x >> 20) - (j + 1)) & 0xFFF) >= 0x800); n++) {
                        if (__any_sync(~0u, lds32v(tk + (((j - 1) & 7) << 4)) == (NO_TILE | (uint32_t)j << 20))) { v.x = NO_TILE; break; }
                        __nanosleep(100); fail_if(n > (1 << 24));
                    }
                    if (__any_sync(~0u, (v.x & NO_TILE) == NO_TILE)) break;
                    j += __reduce_max_sync(~0u, ahead);
                    for (int u = v.w & 0xFFFF; __any_sync(~0u, u < (v.w & 0xFFFF) + (v.w >> 16)); u++) cell(u, (v.x >> 17) & 1);
                }
            } else {
                const uint32_t rtk = HELPER ? tk : mapa(tk, lane < CL ? lane : 0), rfull = HELPER ? bar_full : mapa(bar_full, lane < CL ? lane : 0);
                int s = 0; uint32_t ph = 1;
                uint64_t pol;
                if (!HELPER) asm volatile("createpolicy.fractional.L2::evict_first.b64 %0, 1.0;" : "=l"(pol));
                else asm volatile("createpolicy.fractional.L2::evict_normal.b64 %0, 1.0;" : "=l"(pol));
                auto request = [&](int j, const uint4& t) {
                    const bool valid = t.x != NO_TILE;
                    const CUtensorMap* tm = &maps.x[(t.x >> 14) & 1];
                    mbar_wait(bar_empty + 8 * s, ph);
                    if (__any_sync(~0u, valid)) {
                        const uint32_t dst = sb + OFF_X + s * TILE_BYTES;
                        if (HELPER)
                            asm volatile("{\n.reg .pred p;\nelect.sync _|p, 0xffffffff;\n"
                                         "@p cp.async.bulk.tensor.4d.shared::cluster.global.mbarrier::complete_tx::bytes.L2::cache_hint [%0], [%4, {%6, %7, %6, %6}], [%5], %11;\n"
                                         "@p cp.async.bulk.tensor.4d.shared::cluster.global.mbarrier::complete_tx::bytes.L2::cache_hint [%1], [%4, {%6, %8, %6, %6}], [%5], %11;\n"
                                         "@p cp.async.bulk.tensor.4d.shared::cluster.global.mbarrier::complete_tx::bytes.L2::cache_hint [%2], [%4, {%6, %9, %6, %6}], [%5], %11;\n"
                                         "@p cp.async.bulk.tensor.4d.shared::cluster.global.mbarrier::complete_tx::bytes.L2::cache_hint [%3], [%4, {%6, %10, %6, %6}], [%5], %11;\n}\n"
                                         :: "r"(dst), "r"(dst + 9216), "r"(dst + 2 * 9216), "r"(dst + 3 * 9216), "l"(tm), "r"(bar_full + 8 * s), "r"(0),
                                            "r"(t.y & 0xFFFF), "r"(t.y >> 16), "r"(t.z & 0xFFFF), "r"(t.z >> 16), "l"(pol) : "memory");
                        else
                            asm volatile("{\n.reg .pred p;\nelect.sync _|p, 0xffffffff;\n"
                                         "@p cp.async.bulk.tensor.4d.shared::cluster.global.mbarrier::complete_tx::bytes.multicast::cluster.L2::cache_hint [%0], [%4, {%6, %7, %6, %6}], [%5], %11, %12;\n"
                                         "@p cp.async.bulk.tensor.4d.shared::cluster.global.mbarrier::complete_tx::bytes.multicast::cluster.L2::cache_hint [%1], [%4, {%6, %8, %6, %6}], [%5], %11, %12;\n"
                                         "@p cp.async.bulk.tensor.4d.shared::cluster.global.mbarrier::complete_tx::bytes.multicast::cluster.L2::cache_hint [%2], [%4, {%6, %9, %6, %6}], [%5], %11, %12;\n"
                                         "@p cp.async.bulk.tensor.4d.shared::cluster.global.mbarrier::complete_tx::bytes.multicast::cluster.L2::cache_hint [%3], [%4, {%6, %10, %6, %6}], [%5], %11, %12;\n}\n"
                                         :: "r"(dst), "r"(dst + 9216), "r"(dst + 2 * 9216), "r"(dst + 3 * 9216), "l"(tm), "r"(bar_full + 8 * s), "r"(0),
                                            "r"(t.y & 0xFFFF), "r"(t.y >> 16), "r"(t.z & 0xFFFF), "r"(t.z >> 16), "h"((uint16_t)((1u << CL) - 1)), "l"(pol) : "memory");
                    }
                    if (HELPER) {
                        if (lane == 0) { sts128(tk + ((j & 7) << 4), t); mbar_expect_tx(bar_full + 8 * s, valid ? TILE_BYTES : 0); }
                    } else if (lane < CL) {
                        asm volatile("mbarrier.arrive.expect_tx.shared::cluster.b64 _, [%0], %1;" :: "r"(rfull + 8 * s), "r"(valid ? TILE_BYTES + 16 : 16) : "memory");
                        asm volatile("st.async.weak.shared::cluster.mbarrier::complete_tx::bytes.v4.u32 [%0], {%1, %2, %3, %4}, [%5];"
                                     :: "r"(rtk + ((j & 7) << 4)), "r"(t.x | ((uint32_t)(j + 1) << 20)), "r"(t.y), "r"(t.z), "r"(t.w), "r"(rfull + 8 * s) : "memory");
                    }
                    if (++s == NSLOT) { s = 0; ph ^= 1; }
                };
                if (HELPER) {
#pragma unroll 1
                    for (int j = 0; j < XEARLY; j++) request(j, entry_w(p, p.ncl + cid + (j >> 1) * (p.ncl + p.nh), j & 1, j & 1, 0));
                    mbar_wait(sb + OFF_PLAN, 0);
                    mbar_wait(sb + OFF_GO, 0);
                    for (int j = XEARLY;; j++) {
                        const uint4 t = lds128v(sb + OFF_TAB + 16 * (j - XEARLY));
                        request(j, t);
                        if (__any_sync(~0u, t.x == NO_TILE)) break;
                    }
                } else {
                    static_assert(XEARLY == 2, "");
                    request(0, e0);
                    request(1, e1);
                    mbar_wait(sb + OFF_PLAN, 0);
                    const uint4 inf = lds128v(sb + OFF_INFO);
                    const unsigned long long plan = inf.x | ((unsigned long long)inf.y << 32);
                    const int side = inf.z & 1, nc = inf.z >> 16;
                    const int nh = helpers(p, plan, side), rm = p.rm[nh], rmo = p.rm[p.nh - nh];
                    const uint32_t ratio = p.ratio[nh], ratioo = p.ratio[p.nh - nh];
                    const int st = NSTAT * nc, sto = NSTAT * (p.ncl - nc);
                    uint4 t = lds128v(sb + OFF_TAB + 16 * ((inf.z >> 8) & 0xFF));
                    mbar_wait(sb + OFF_GO, 0);
                    int j = XEARLY;
#pragma unroll 1
                    for (; j < XEARLY + NSTAT - 2; j++) {
                        const uint4 tn = lds128v(sb + OFF_TAB + 16 * (((inf.z >> 8) & 0xFF) + (j + 1 - XEARLY) * nc));
                        request(j, t);
                        t = tn;
                    }
                    uint32_t drawn = 0;
                    int q = side;
                    request(j++, t);
                    draw(drawn, &g_ticket, 1u << (16 * side));
                    t = lds128v(sb + OFF_TAB + 16 * (((inf.z >> 8) & 0xFF) + (NSTAT - 1) * nc));
                    mbar_wait(sb + OFF_PLAN2, 0);
                    for (;; j++) {
                        request(j, t);
                        uint32_t v = __reduce_max_sync(~0u, drawn);
                        int m = st + ((v >> (16 * side)) & 0xFFFF), mo = sto + ((v >> (16 - 16 * side)) & 0xFFFF);
                        if (q == side ? m >= rm && mo < rmo : mo >= rmo && m < rm) {
                            q ^= 1;
                            draw(drawn, &g_ticket, 1u << (16 * q));
                            v = __reduce_max_sync(~0u, drawn);
                            m = st + ((v >> (16 * side)) & 0xFFFF); mo = sto + ((v >> (16 - 16 * side)) & 0xFFFF);
                        }
                        if (q == side ? m >= rm : mo >= rmo) break;
                        const bool own = q == side;
                        q = m + ((m * ratio) >> 16) > mo + ((mo * ratioo) >> 16) + DELTA ? side ^ 1 : side;
                        draw(drawn, &g_ticket, 1u << (16 * q));
                        if (own) t = lds128v(sb + OFF_TAB + 16 * m);
                        else t = cl_entry(p, mo, side ^ 1, ratioo, plan);
                    }
                    t.x = NO_TILE;
                    request(j + 1, t);
                    if (lane == 0 && atomicInc(&g_done, p.ncl - 1) == (uint32_t)p.ncl - 1) g_ticket = 0;
                }
            }
        } else {
            const int g = warp - 13;
            uint64_t spol;
            asm volatile("createpolicy.fractional.L2::evict_first.b64 %0, 1.0;" : "=l"(spol));
            mbar_wait(sb + OFF_GO, 0);
            if (g == 2 && lane == 0 && atomicInc(&g_passed, p.nctas - 1) == (uint32_t)p.nctas - 1) {
#pragma unroll
                for (int m = 0; m < 36; m++) g_ready[m * 32] = 0;
                g_plan = make_ulonglong2(0, 0);
            }
            __syncwarp();
            for (int i = 0;; i++) {
                asm volatile("bar.arrive %0, 160;" :: "r"(12 + g) : "memory");
                asm volatile("bar.sync %0, 160;" :: "r"(1 + g) : "memory");
                const uint4 t = lds128v(tk + ((i & 7) << 4));
                if ((t.x & NO_TILE) == NO_TILE) break;
                const CUtensorMap* tm = &maps.o[(t.x >> 14) & 1];
                const int row[4] = {(int)(t.y & 0xFFFF), (int)(t.y >> 16), (int)(t.z & 0xFFFF), (int)(t.z >> 16)};
                if (lane == 0) {
#pragma unroll
                    for (int k = 0; k < 4; k++)
                        asm volatile("cp.async.bulk.tensor.3d.global.shared::cta.bulk_group.L2::cache_hint [%0, {%2, %3, %4}], [%1], %5;"
                                     :: "l"(tm), "r"(sb + OFF_STG + (g + 3 * (i & 1)) * STG_BYTES + k * 1024), "r"((g * 3 + rank) * 64), "r"(row[k]), "r"(0), "l"(spol) : "memory");
                    asm volatile("cp.async.bulk.commit_group;" ::: "memory");
                    asm volatile("cp.async.bulk.wait_group.read 1;" ::: "memory");
                }
                __syncwarp();
            }
            if (lane == 0) asm volatile("cp.async.bulk.wait_group.read 0;" ::: "memory");
        }
        __syncwarp();
        if (!HELPER) asm volatile("barrier.cluster.arrive.relaxed.aligned;\nbarrier.cluster.wait.aligned;" ::: "memory");
    } else {
        asm volatile("setmaxnreg.inc.sync.aligned.u32 160;");
        const int wg = warp >> 2, wtid = tid & 127;
        if (HELPER) asm volatile("bar.sync 0;" ::: "memory");
        else {
            int prb = cid;
            if (prb >= 36) asm volatile("barrier.cluster.wait.aligned;" ::: "memory");
#pragma unroll 1
            for (int round = 0; prb < 36; prb += p.ncl, round++) {
                const uint32_t wsm = sb + OFF_WST, msk = sb + OFF_MSK + (round & 1) * 288, mbar = sb + OFF_MBAR + (round & 1) * 8;
                if (round) {
                    asm volatile("bar.sync 3, 384;" ::: "memory");
                    if (tid == 0) mbar_expect_tx(mbar, 36 * 8);
                    prep_load(prb >> 2);
                }
                const int nt = ties(wv[0].x, wv[1].x, wv[2].x, wv[3].x) + ties(wv[0].y, wv[1].y, wv[2].y, wv[3].y) +
                               ties(wv[0].z, wv[1].z, wv[2].z, wv[3].z) + ties(wv[0].w, wv[1].w, wv[2].w, wv[3].w);
                const uint32_t mk = __ballot_sync(~0u, nt > 0), md = __ballot_sync(~0u, nt > 1);
                if (round == 0) asm volatile("barrier.cluster.wait.aligned;" ::: "memory");
                if (lane < CL)
                    asm volatile("st.async.weak.shared::cluster.mbarrier::complete_tx::bytes.v2.u32 [%0], {%1, %2}, [%3];"
                                 :: "r"(mapa(msk + (rank * 12 + warp) * 8, lane)), "r"(mk), "r"(md), "r"(mapa(mbar, lane)) : "memory");
#pragma unroll
                for (int j = 0; j < 4; j++) {
                    const int row = wrow + j;
                    const uint32_t ad = wsm + row * 128 + (((lane >> 2) ^ ((row & 1) | ((row >> 1) & 6))) << 4);
                    asm volatile("st.shared.v4.b32 [%0], {%1,%2,%3,%4};" :: "r"(ad), "r"(wv[j].x), "r"(wv[j].y), "r"(wv[j].z), "r"(wv[j].w) : "memory");
                }
                if (warp == 0) {
                    mbar_wait(mbar, (round >> 1) & 1);
                    uint4 ms = make_uint4(0, 0, 0, 0);
                    if (lane < KSTEPS) ms = lds128v(msk + 16 * lane);
                    const uint32_t te = (ms.x & 0x0F0F0F0Fu) | ((ms.z & 0x0F0F0F0Fu) << 4), to = ((ms.x >> 4) & 0x0F0F0F0Fu) | (ms.z & 0xF0F0F0F0u);
                    const uint32_t de = (ms.y & 0x0F0F0F0Fu) | ((ms.w & 0x0F0F0F0Fu) << 4), dq = ((ms.y >> 4) & 0x0F0F0F0Fu) | (ms.w & 0xF0F0F0F0u);
                    auto count = [](uint32_t v) { v -= (v >> 1) & 0x55555555u; v = (v & 0x33333333u) + ((v >> 2) & 0x33333333u); return (v + (v >> 4)) & 0x0F0F0F0Fu; };
                    const uint32_t c0 = __reduce_add_sync(~0u, count(te)), c1 = __reduce_add_sync(~0u, count(to));
                    auto byte = [](uint32_t a, uint32_t b, uint32_t u) { return __byte_perm(a, b, (u >> 1) + 4 * (u & 1)) & 0xFFu; };
                    const uint32_t ku = byte(c0, c1, lane & 7) * 8 + (lane & 7), k2 = 2 * (lane >> 3);
                    const uint32_t ranks = __reduce_add_sync(~0u, ((byte(c0, c1, k2) * 8 + k2 < ku) + (byte(c0, c1, k2 + 1) * 8 + k2 + 1 < ku)) << (4 * (lane & 7)));
                    const uint32_t order = __reduce_add_sync(~0u, lane < 8 ? lane << (4 * ((ranks >> (4 * lane)) & 7)) : 0);
                    int cnt[4]; uint32_t mq = 0;
#pragma unroll
                    for (int z = 0; z < 4; z++) {
                        const uint32_t ua = (order >> (4 * z)) & 7, ub = (order >> (28 - 4 * z)) & 7;
                        const uint32_t ta = byte(te, to, ua), tb = byte(te, to, ub), v = ta | tb | ((ta & tb) | byte(de, dq, ua) | byte(de, dq, ub)) << 8;
                        cnt[z] = __popc(v);
                        if (z == (prb & 3)) mq = v;
                    }
                    const uint32_t l01 = __reduce_add_sync(~0u, cnt[0] | cnt[1] << 16), l23 = __reduce_add_sync(~0u, cnt[2] | cnt[3] << 16);
                    const int ulo = (order >> (4 * (prb & 3))) & 7, uhi = (order >> (28 - 4 * (prb & 3))) & 7;
                    const int full = max(max(max((int)(l01 & 0xFFFF) - cnt[0], (int)(l01 >> 16) - cnt[1]), max((int)(l23 & 0xFFFF) - cnt[2], (int)(l23 >> 16) - cnt[3])), 16);
                    const uint32_t more = (65 - cnt[0] - cnt[1] - cnt[2] - cnt[3]) << 5 | lane;
                    const uint32_t best = __reduce_min_sync(~0u, lane < KSTEPS ? full << 12 | more : full << 12 | 31);
                    const int twice = best & 31;
                    int twice2 = 31;
                    if (best >> 12 > 16 && twice < KSTEPS) {
                        const uint32_t r01 = l01 - __shfl_sync(~0u, cnt[0] | cnt[1] << 16, twice), r23 = l23 - __shfl_sync(~0u, cnt[2] | cnt[3] << 16, twice);
                        const int full2 = max(max((int)(r01 & 0xFFFF) - cnt[0], (int)(r01 >> 16) - cnt[1]), max((int)(r23 & 0xFFFF) - cnt[2], (int)(r23 >> 16) - cnt[3]));
                        twice2 = __reduce_min_sync(~0u, lane < KSTEPS && lane != twice ? max(full2, 16) << 12 | more : ~0u) & 31;
                    }
                    sts32(sb + OFF_SEL + 4 * lane, lane == 31 ? ulo | (uhi << 4) | (twice << 8) | (twice2 << 13) : lane == twice || lane == twice2 ? 0 : mq);
                }
                asm volatile("bar.sync 1, 384;" ::: "memory");
                const uint32_t units = lds32v(sb + OFF_SEL + 4 * 31), mq = lds32v(sb + OFF_SEL + 4 * min(lane, 30));
                uint32_t wm[4];
                load_units(wsm, warp, units & 7, (units >> 4) & 7, lane, wm);
                emit_half(wm, mq, prb, rank * 6 + (warp >> 1), warp & 1, lane, units, b0, b1);
                asm volatile("bar.sync 2, 384;" ::: "memory");
                if (tid == 0) asm volatile("red.release.gpu.global.add.u32 [%0], 1;" :: "l"(&g_ready[prb * 32]) : "memory");
            }
            if (warp == 0 && lane < CL) mbar_arrive_cluster(mapa(sb + OFF_GO, lane));
        }
        const int mt = wg * 3 + rank, rb = mt * 4 + (warp & 3);
        {
            uint32_t v; int n = 0;
            do { asm volatile("ld.acquire.gpu.global.u32 %0, [%1];" : "=r"(v) : "l"(&g_ready[rb * 32]) : "memory"); fail_if(++n > (1 << 22)); } while (__any_sync(~0u, v < CL));
        }
        if (wg > 0) asm volatile("bar.sync %0, 256;" :: "r"(7 + wg) : "memory");
        uint32_t a[KSTEPS + 2][4], meta[9];
        uint2 rv[3]; uint32_t ro[3], sel[3];
        uint32_t info, bias_lo, bias_hi;
        {
            const uint4* ap = g_aux + rb * 6 * 32 + lane;
            const uint4 v3 = ldw(ap + 96), v2 = ldw(ap + 64), v4 = ldw(ap + 128), v5 = ldw(ap + 160), v0 = ldw(ap), v1 = ldw(ap + 32);
            meta[0] = v0.x; meta[1] = v0.y; meta[2] = v0.z; meta[3] = v0.w; meta[4] = v1.x; meta[5] = v1.y; meta[6] = v1.z; meta[7] = v1.w;
            meta[8] = v2.x; info = v2.y; bias_lo = v2.z; bias_hi = v2.w;
            ro[0] = v3.x; ro[1] = v3.y; ro[2] = v3.z;
            rv[0] = make_uint2(v4.x, v4.y); rv[1] = make_uint2(v4.z, v4.w); rv[2] = make_uint2(v5.x, v5.y);
        }
#pragma unroll
        for (int k = 0; k < KSTEPS + 1; k++) { uint4 v = ldw(&g_afrag[(mt * (KSTEPS + 2) + k) * 128 + wtid]); a[k][0] = v.x; a[k][1] = v.y; a[k][2] = v.z; a[k][3] = v.w; }
        if (wg < 2) asm volatile("bar.arrive %0, 256;" :: "r"(8 + wg) : "memory");
        if (lane == 0) mbar_arrive(sb + OFF_GO);
        auto selector = [](uint32_t o) { return 0x5410u + ((o >> 15) & 1) * 0x22u + (o >> 31) * 0x2200u; };
#pragma unroll
        for (int j = 0; j < 3; j++) { sel[j] = selector(ro[j]); ro[j] &= 0x7FFF7FFFu; }
        mbar_wait(bar_full, 0);
        info = __shfl_sync(~0u, info, 0);
        const int ngrp = info & 0xFF, ulo = (info >> 8) & 7, uhi = (info >> 12) & 7;
        const uint32_t stg = sb + OFF_STG + wg * STG_BYTES + ((lane >> 4) * 8 + (lane & 7)) * 128 + (((((lane >> 3) & 1) ? uhi : ulo) ^ (lane & 7)) << 4);
        const uint32_t twice = (((info >> 17) & 15) * 1024 + ((info >> 16) & 1) * 64) >> 4;
        const uint32_t twice2 = (((info >> 22) & 15) * 1024 + ((info >> 21) & 1) * 64) >> 4;
        const uint32_t rempty = HELPER ? bar_empty : mapa(bar_empty, 0);
        float acc[NACC];
        uint32_t bq[NB][6];
        auto gather = [&](uint32_t xb) {
#pragma unroll
            for (int j = 0; j < 4; j++) {
                const uint32_t o = xb + ((j & 1) ? ro[j >> 1] >> 16 : ro[j >> 1] & 0xFFFF);
#pragma unroll
                for (int n = 0; n < NB; n++) {
                    if (j < 3) { bq[n][j] = lds32(o + n * 9216); continue; }
                    bq[n][j] = 0;
                    asm volatile("{\n.reg .pred p;\nsetp.lt.s32 p, %2, %3;\n@p ld.shared.b32 %0, [%1];\n}" : "+r"(bq[n][j]) : "r"(o + n * 9216), "r"(j), "r"(ngrp) : "memory");
                }
            }
        };
        auto select = [&]() {
#pragma unroll
            for (int n = 0; n < NB; n++)
#pragma unroll
                for (int j = 0; j < 2; j++) bq[n][2 * j] = __byte_perm(bq[n][2 * j], bq[n][2 * j + 1], sel[j]);
        };
        auto further = [&](uint32_t xb, int bar) {
#pragma unroll 1
            for (int y = 4; y < min(ngrp, 5); y++) {
#pragma unroll
                for (int n = 0; n < NB; n++) { bq[n][4] = lds32(xb + (ro[2] & 0xFFFF) + n * 9216); bq[n][5] = lds32(xb + (ro[2] >> 16) + n * 9216); }
#pragma unroll
                for (int n = 0; n < NB; n++) mma_k8(acc + 4 * n, rv[2], __byte_perm(bq[n][4], bq[n][5], sel[2]));
                if (bar >= 0) asm volatile("bar.arrive %0, 256;" :: "r"(bar) : "memory");
#pragma unroll 1
                for (int z = 3; 2 * z < ngrp; z++) {
                    const uint2 v = __ldca(&g_rval[(rb * 36 + z) * 32 + lane]); const uint32_t off = __ldca(&g_roff[(rb * 36 + z) * 32 + lane]);
                    uint32_t bx[NB];
#pragma unroll
                    for (int n = 0; n < NB; n++) bx[n] = __byte_perm(lds32(xb + (off & 0x7FFF) + n * 9216), lds32(xb + ((off >> 16) & 0x7FFF) + n * 9216), selector(off));
#pragma unroll
                    for (int n = 0; n < NB; n++) mma_k8(acc + 4 * n, v, bx[n]);
                }
            }
        };
        bool more = true;
#pragma unroll
        for (int n = 0; n < NB; n++) bq[n][4] = bq[n][5] = 0;
        gather(sb + OFF_X);
        select();
#pragma unroll
        for (int n = 0; n < NB; n++) mma_k16(acc + 4 * n, rv[0], rv[1], bq[n][0], bq[n][2], 0.f, 0.f, 0.f, 0.f);
        further(sb + OFF_X, -1);
        const int bar_a = 8 + wg, bar_an = 8 + (wg + 2) % 3, bar_tn = 4 + (wg + 2) % 3;
        if (wg == 1) asm volatile("bar.arrive 4, 256;" ::: "memory");
        if (wg == 2) { asm volatile("bar.sync 10, 256;" ::: "memory"); asm volatile("bar.arrive 5, 256;" ::: "memory"); }
        auto run = [&](auto tw) {
        constexpr int TW = decltype(tw)::value;
        int s = 0; uint32_t ph = 0;
        bool ready = false;
        for (int i = 0; more; i++) {
            const uint32_t xb = sb + OFF_X + s * TILE_BYTES;
            const int s1 = s + 1 == NSLOT ? 0 : s + 1;
            const uint32_t ph1 = s1 == 0 ? ph ^ 1 : ph;
            asm volatile("bar.sync %0, 256;" :: "r"(4 + wg) : "memory");
            const uint64_t desc = ((uint64_t)1 << 62) | ((uint64_t)(9216 >> 4) << 32) | ((uint64_t)1 << 16) | (uint64_t)(xb >> 4);
            asm volatile("wgmma.fence.sync.aligned;" ::: "memory");
#pragma unroll
            for (int k = 0; k < KSTEPS; k++) {
                const uint64_t d = desc + (uint64_t)(((k >> 1) * 1024 + (k & 1) * 64) >> 4);
                if (k & 1) wgmma_sp<1>(acc, a[k], d, meta[k >> 1]);
                else       wgmma_sp<0>(acc, a[k], d, meta[k >> 1]);
            }
            if (TW > 0) wgmma_sp<0>(acc, a[KSTEPS], desc + twice, 0x44444444u);
            if (TW > 1) wgmma_sp<0>(acc, a[KSTEPS + 1], desc + twice2, 0x44444444u);
            asm volatile("wgmma.commit_group.sync.aligned;" ::: "memory");
            asm volatile("bar.arrive %0, 256;" :: "r"(bar_an) : "memory");
            if (!ready) mbar_wait(bar_full + 8 * s1, ph1);
            const uint32_t tn = lds32v(tk + (((i + 1) & 7) << 4));
            gather(sb + OFF_X + s1 * TILE_BYTES);
            asm volatile("bar.sync %0, 160;" :: "r"(12 + wg) : "memory");
            asm volatile("wgmma.wait_group.sync.aligned 0;" ::: "memory");
            const uint32_t sg = stg + (i & 1) * (3 * STG_BYTES);
            if (wtid == 0) { if (HELPER) mbar_arrive(bar_empty + 8 * s); else mbar_arrive_cluster(rempty + 8 * s); }
#pragma unroll
            for (int n = 0; n < NB; n += 2) {
                const uint32_t p0 = pack_bias(acc[4 * n], acc[4 * n + 1], bias_lo), p1 = pack_bias(acc[4 * n + 2], acc[4 * n + 3], bias_hi);
                const uint32_t p2 = pack_bias(acc[4 * n + 4], acc[4 * n + 5], bias_lo), p3 = pack_bias(acc[4 * n + 6], acc[4 * n + 7], bias_hi);
                if (n == 0) asm volatile("stmatrix.sync.aligned.m8n8.x4.trans.shared.b16 [%0], {%1,%2,%3,%4};" :: "r"(sg + n * 1024), "r"(p0), "r"(p1), "r"(p2), "r"(p3) : "memory");
                else asm volatile("{\n.reg .pred p;\nAGAIN:\nstmatrix.sync.aligned.m8n8.x4.trans.shared.b16 [%0], {%1,%2,%3,%4};\nsetp.eq.u32 p, %5, 0xFFFFFFFE;\n@p bra.uni AGAIN;\n}"
                                  :: "r"(sg + n * 1024), "r"(p0), "r"(p1), "r"(p2), "r"(p3), "r"(info) : "memory");
            }
            more = __any_sync(~0u, (tn & NO_TILE) != NO_TILE);
            select();
            if (wg != 2 || more) {
                asm volatile("{\n.reg .pred p;\nTURN:\nbar.sync %0, 256;\nsetp.eq.u32 p, %1, 0xFFFFFFFF;\n@p bra.uni TURN;\n}" :: "r"(bar_a), "r"(info) : "memory");
#pragma unroll
                for (int n = 0; n < NB; n++) {
                    mma_k16(acc + 4 * n, rv[0], rv[1], bq[n][0], bq[n][2], 0.f, 0.f, 0.f, 0.f);
                    if (n == 0) asm volatile("{\n.reg .pred p;\nsetp.le.s32 p, %1, 4;\n@p bar.arrive %0, 256;\n}" :: "r"(bar_tn), "r"(ngrp) : "memory");
                }
                further(sb + OFF_X + s1 * TILE_BYTES, bar_tn);
            }
            asm volatile("fence.proxy.async.shared::cta;" ::: "memory");
            asm volatile("bar.arrive %0, 160;" :: "r"(1 + wg) : "memory");
            s = s1; ph = ph1;
            ready = __all_sync(~0u, mbar_test(bar_full + 8 * (s + 1 == NSLOT ? 0 : s + 1), s + 1 == NSLOT ? ph ^ 1 : ph));
        }
        };
        if (((info >> 16) & 31) >= KSTEPS) run(Num<0>());
        else if (((info >> 21) & 31) >= KSTEPS) run(Num<1>());
        else {
            const uint4 v = ldw(&g_afrag[(mt * (KSTEPS + 2) + KSTEPS + 1) * 128 + wtid]);
            a[KSTEPS + 1][0] = v.x; a[KSTEPS + 1][1] = v.y; a[KSTEPS + 1][2] = v.z; a[KSTEPS + 1][3] = v.w;
            run(Num<2>());
        }
        if (wg == 0) asm volatile("bar.sync 4, 256;" ::: "memory");
        asm volatile("bar.sync %0, 160;" :: "r"(12 + wg) : "memory");
        asm volatile("bar.arrive %0, 160;" :: "r"(1 + wg) : "memory");
        if (!HELPER) asm volatile("barrier.cluster.arrive.relaxed.aligned;\nbarrier.cluster.wait.aligned;" ::: "memory");
    }
}

typedef CUresult (*EncodeFn)(CUtensorMap*, CUtensorMapDataType, cuuint32_t, void*, const cuuint64_t*, const cuuint64_t*, const cuuint32_t*, const cuuint32_t*,
                             CUtensorMapInterleave, CUtensorMapSwizzle, CUtensorMapL2promotion, CUtensorMapFloatOOBfill);

__global__ void plain_kernel(const __nv_bfloat16* x, const __nv_bfloat16* w, const __nv_bfloat16* b, __nv_bfloat16* out, int ntok) {
    const int t0 = blockIdx.x * 8;
    for (int f = threadIdx.x; f < D; f += blockDim.x) {
        float acc[8] = {};
        for (int g = 0; g < D / 4; g++) {
            float v[4], m[4];
            for (int i = 0; i < 4; i++) { v[i] = __bfloat162float(w[(4 * g + i) * D + f]); m[i] = fabsf(v[i]); }
            const float thr = fmaxf(fminf(fmaxf(m[0], m[1]), fmaxf(m[2], m[3])), fmaxf(fminf(m[0], m[1]), fminf(m[2], m[3])));
            for (int i = 0; i < 4; i++)
                for (int t = 0; t < 8; t++)
                    if (m[i] >= thr && t0 + t < ntok) acc[t] += v[i] * __bfloat162float(x[(size_t)(t0 + t) * D + 4 * g + i]);
        }
        for (int t = 0; t < 8; t++)
            if (t0 + t < ntok) out[(size_t)(t0 + t) * D + f] = __hadd(__float2bfloat16(acc[t]), b[f]);
    }
}

extern "C" void kernel_launch(void* const* d_in, const int* in_sizes, int n_in, void* d_out, int out_size) {
    static EncodeFn enc = nullptr;
    static int ncl = 0, nhelp = 0;
    const int ntok = in_sizes[0] / D;
    cudaLaunchConfig_t cfg = {};
    cudaLaunchAttribute at[1];
    at[0].id = cudaLaunchAttributeClusterDimension; at[0].val.clusterDim.x = CL; at[0].val.clusterDim.y = 1; at[0].val.clusterDim.z = 1;
    cfg.blockDim = dim3(NTHREADS); cfg.dynamicSmemBytes = SMEM_BYTES; cfg.attrs = at; cfg.numAttrs = 1; cfg.stream = cudaStreamPerThread;
    if (!enc) {
        cudaDriverEntryPointQueryResult qr; void* fn = nullptr;
        cudaGetDriverEntryPoint("cuTensorMapEncodeTiled", &fn, cudaEnableDefault, &qr);
        enc = (EncodeFn)fn;
        cudaFuncSetAttribute(spgemm_kernel<false>, cudaFuncAttributeMaxDynamicSharedMemorySize, SMEM_BYTES);
        cudaFuncSetAttribute(spgemm_kernel<true>, cudaFuncAttributeMaxDynamicSharedMemorySize, SMEM_BYTES);
        int dev = 0, nsm = 0;
        cudaGetDevice(&dev);
        cudaDeviceGetAttribute(&nsm, cudaDevAttrMultiProcessorCount, dev);
        cfg.gridDim = dim3(CL * (nsm / CL));
        cudaOccupancyMaxActiveClusters(&ncl, spgemm_kernel<false>, &cfg);
        if (ncl < 1) ncl = 1;
        nhelp = nsm > CL * ncl ? (nsm - CL * ncl) / CL : 0;
        if (nhelp > 7) nhelp = 7;
    }
    if (ntok % 4096 || ntok < 16384 || ntok > 65536 || ncl < 2 || ncl > 56 || ncl < CL * nhelp || 8 * (ncl + nhelp) > ntok / 64) {
        plain_kernel<<<(ntok + 7) / 8, 192, 0, cudaStreamPerThread>>>((const __nv_bfloat16*)d_in[0], (const __nv_bfloat16*)d_in[1], (const __nv_bfloat16*)d_in[2], (__nv_bfloat16*)d_out, ntok);
        return;
    }
    Maps maps;
    for (int v = 0; v < 2; v++) {
        const cuuint32_t rows = v == 0 ? 2 : 1;
        const cuuint64_t pitch = (v == 0 ? 14 : 57) * D * 2;
        {
            cuuint64_t dims[4] = {64, (cuuint64_t)ntok, 8 / rows, 9};
            cuuint64_t strides[3] = {D * 2, pitch, 128};
            cuuint32_t box[4] = {64, rows, 8 / rows, 9}, es[4] = {1, 1, 1, 1};
            enc(&maps.x[v], CU_TENSOR_MAP_DATA_TYPE_BFLOAT16, 4, d_in[0], dims, strides, box, es, CU_TENSOR_MAP_INTERLEAVE_NONE,
                CU_TENSOR_MAP_SWIZZLE_128B, CU_TENSOR_MAP_L2_PROMOTION_L2_128B, CU_TENSOR_MAP_FLOAT_OOB_FILL_NONE);
        }
        {
            cuuint64_t dims[3] = {D, (cuuint64_t)ntok, 8 / rows};
            cuuint64_t strides[2] = {D * 2, pitch};
            cuuint32_t box[3] = {64, rows, 8 / rows}, es[3] = {1, 1, 1};
            enc(&maps.o[v], CU_TENSOR_MAP_DATA_TYPE_BFLOAT16, 3, d_out, dims, strides, box, es, CU_TENSOR_MAP_INTERLEAVE_NONE,
                CU_TENSOR_MAP_SWIZZLE_128B, CU_TENSOR_MAP_L2_PROMOTION_NONE, CU_TENSOR_MAP_FLOAT_OOB_FILL_NONE);
        }
    }
    {
        cuuint64_t dims[3] = {256, (cuuint64_t)ntok * D * 2 / 2048, 4};
        cuuint64_t strides[2] = {2048, 16384};
        cuuint32_t box[3] = {256, 4, 4}, es[3] = {1, 1, 1};
        enc(&maps.pf, CU_TENSOR_MAP_DATA_TYPE_FLOAT64, 3, d_in[0], dims, strides, box, es, CU_TENSOR_MAP_INTERLEAVE_NONE,
            CU_TENSOR_MAP_SWIZZLE_NONE, CU_TENSOR_MAP_L2_PROMOTION_NONE, CU_TENSOR_MAP_FLOAT_OOB_FILL_NONE);
    }
    Params p;
    p.w = (const uint16_t*)d_in[1]; p.bias = (const uint16_t*)d_in[2]; p.x = (const uint8_t*)d_in[0];
    p.nq = ntok / 64; p.npages = (int)(((size_t)ntok * D * 2) >> 21);
    p.rot = ntok / 4096 * 3 / 4; p.wrap = 9 * (ntok / 4096 - p.rot);
    const int nc = ncl, nh = nhelp;
    p.ncl = nc; p.nh = nh; p.nctas = CL * (nc + nh);
    p.m0 = (nc + nh) * XEARLY / 2;
    for (int h = 0; h < 8; h++) {
        const uint32_t R = p.nq - p.m0, H = h * (HT * p.nq / 1024 * 44 / (nc + nh));
        p.ratio[h] = h <= nh ? (H << 16) / (R - H) : 0;
        p.rm[h] = p.ratio[h] ? (((R - 1) << 16) + 0x7FFFu) / (0x10000u + p.ratio[h]) + 1 : R;
    }
    p.c0 = (p.m0 * 9) >> 3;
    p.tb = p.m0 + (NSLOT - XEARLY) * (nc + nh) / 2;
    p.ta = p.tb + 1 + (int)((p.nq - p.tb) * TAFRAC); p.te = (int)(p.nq * TEFRAC) + 2;
    p.slope0 = ((LEAD1 - LEAD0) << 16) / (p.ta - p.tb); p.slope1 = ((LEAD1 - LEADE) << 16) / (p.te - p.ta);
    cfg.gridDim = dim3(CL * nc);
    cudaLaunchKernelEx(&cfg, spgemm_kernel<false>, p, maps);
    if (nh) {
        at[0].id = cudaLaunchAttributeProgrammaticStreamSerialization; at[0].val.programmaticStreamSerializationAllowed = 1;
        cfg.gridDim = dim3(CL * nh);
        cudaLaunchKernelEx(&cfg, spgemm_kernel<true>, p, maps);
    }
}
```
